```python
import torch

def _softmax(x, axis=-1):
    return torch.softmax(x, dim=axis)
def _gelu(x):
    return torch.nn.functional.gelu(x, approximate="tanh")
def _silu(x):
    return torch.nn.functional.silu(x)
def _sigmoid(x):
    return torch.sigmoid(x)
def _layernorm(x, axis=-1, eps=1e-5):
    m = x.mean(dim=axis, keepdim=True)
    v = x.var(dim=axis, keepdim=True, unbiased=False)
    return (x - m) / torch.sqrt(v + eps)
def _scatter_add(tgt, idx, src, axis=0):
    return tgt.clone().index_add_(axis, idx, src)
def _segment_sum(src, seg, n):
    out = torch.zeros((n,) + src.shape[1:], dtype=src.dtype)
    return out.index_add_(0, seg, src)
def _pad(x, pw):
    flat = tuple(v for pair in reversed(pw) for v in pair)
    return torch.nn.functional.pad(x, flat)

kernel_name = 'interleave_layers__sliding_block_cached__glu_gated_swiglu__decode'

def setup_inputs():

    _w = (lambda a: (lambda t: t.to(torch.bfloat16) if t.is_floating_point() else t)(torch.as_tensor(a)))
    def _A_setup():
        B, Sq, D = 1, 1, 512
        Hq, Hkv, Sk, Dh = 32, 8, 32768, 128
        assert Hq % Hkv == 0, (Hq, Hkv)
        return {
            "x": _w((lambda *s: torch.randn(*s, dtype=torch.bfloat16) * 0.05)(B, Sq, D)),
            "k_cache": _w((lambda *s: torch.randn(*s, dtype=torch.bfloat16) * 0.8)(B, Hkv, Sk, Dh)),
            "v_cache": _w((lambda *s: torch.randn(*s, dtype=torch.bfloat16) * 0.8)(B, Hkv, Sk, Dh)),
            "wq": _w((lambda *s: torch.randn(*s, dtype=torch.bfloat16) * 0.8)(D, Hq * Dh) * (D ** -0.5)),
            "wo": _w((lambda *s: torch.randn(*s, dtype=torch.bfloat16) * 0.8)(Hq * Dh, D) * ((Hq * Dh) ** -0.5)),
        }
    _A_in = _A_setup()

    def _B_setup():
        B, S, D, F = 1, 1, 512, 1792
        return {
            "x": _w((lambda *s: torch.randn(*s, dtype=torch.bfloat16) * 0.05)(B, S, D)),
            "w1": _w((lambda *s: torch.randn(*s, dtype=torch.bfloat16) * 0.2)(D, F) * (2.0 / D) ** 0.5),
            "w3": _w((lambda *s: torch.randn(*s, dtype=torch.bfloat16) * 0.2)(D, F) * (2.0 / D) ** 0.5),
            "w2": _w((lambda *s: torch.randn(*s, dtype=torch.bfloat16) * 0.2)(F, D) * (2.0 / F) ** 0.5),
        }
    _B_in = _B_setup()

    return {
        "A_x": _A_in["x"],
        "A_k_cache": _A_in["k_cache"],
        "A_v_cache": _A_in["v_cache"],
        "A_wq": _A_in["wq"],
        "A_wo": _A_in["wo"],
        "B_x": _B_in["x"],
        "B_w1": _B_in["w1"],
        "B_w3": _B_in["w3"],
        "B_w2": _B_in["w2"],
    }

def reference(A_x, A_k_cache, A_v_cache, A_wq, A_wo, B_x, B_w1, B_w3, B_w2):
    def _A_ref(x, k_cache, v_cache, wq, wo):
        B, Sq, D = x.shape
        Hq, Dh = 32, 128
        Hkv, Sk = k_cache.shape[1], k_cache.shape[2]
        W = min(4096, max(256, Sk // 4))
        rep = Hq // Hkv
        q = (lambda x, *d: x.permute(*d))((x @ wq).reshape(B, Sq, Hq, Dh), 0, 2, 1, 3)
        k = (lambda x, n, axis: torch.repeat_interleave(x, n, dim=axis))(k_cache[:, :, Sk - W:, :], rep, axis=1)
        v = (lambda x, n, axis: torch.repeat_interleave(x, n, dim=axis))(v_cache[:, :, Sk - W:, :], rep, axis=1)
        scores = torch.einsum("bhqd,bhkd->bhqk", q, k) * (Dh ** -0.5)
        p = _softmax(scores, axis=-1)
        o = torch.einsum("bhqk,bhkd->bhqd", p, v)
        return (lambda x, *d: x.permute(*d))(o, 0, 2, 1, 3).reshape(B, Sq, Hq * Dh) @ wo

    def _B_ref(x, w1, w3, w2):
        gate = torch.einsum("bsd,df->bsf", x, w1)
        up = torch.einsum("bsd,df->bsf", x, w3)
        h = _silu(gate) * up
        out = torch.einsum("bsf,fd->bsd", h, w2)
        return out

    x = A_x
    x = x + _A_ref(_layernorm(x, axis=-1), A_k_cache, A_v_cache, A_wq, A_wo)
    x = x + _B_ref(_layernorm(x, axis=-1), B_w1, B_w3, B_w2)
    x = x + _A_ref(_layernorm(x, axis=-1), A_k_cache, A_v_cache, A_wq, A_wo)
    x = x + _B_ref(_layernorm(x, axis=-1), B_w1, B_w3, B_w2)
    return x
```

```cpp
#include <cuda_runtime.h>
#include <cuda_bf16.h>
#include <cuda.h>
#include <stdint.h>

namespace {

typedef unsigned long long u64;
typedef __nv_bfloat16 bf16;

constexpr int D_ = 512, HKV_ = 8, SK_ = 32768, DH_ = 128, WIN_ = 4096, FF_ = 1792;
constexpr int CL = 8;
constexpr int NA = 8, NF = 7;
constexpr int NT = 256;
constexpr float LN_EPS = 1e-5f;
constexpr float QSCALE = 0.08838834764831845f * 1.4426950408889634f;
constexpr int SPIN_LIMIT = 1 << 22;

constexpr int SM_KV = 0;
constexpr int SM_W = 131072;
constexpr int SM_W1 = 0, SM_W3 = 32768, SM_W2 = 65536;
constexpr int SCR = 196608;
constexpr int SM_RS0 = SCR;
constexpr int SM_RS1 = SCR + 4096;
constexpr int SM_RS2 = SCR + 6144;
constexpr int SM_LNST = SCR + 8192;
constexpr int SM_OST = SCR + 8256;
constexpr int SM_XB0 = SCR + 8512;
constexpr int SM_XB1 = SCR + 8640;
constexpr int SM_QB = SCR + 8768;
constexpr int SM_WMAX = SCR + 10048;
constexpr int SM_MREF = SCR + 10176;
constexpr int SM_FLAG = SCR + 10192;
constexpr int SM_PART = SCR + 10240;
constexpr int PSTR = 2048 + 64;
constexpr int SM_BAR = SM_PART + 8 * PSTR;
constexpr int SM_TLB = SM_BAR + 512;
constexpr int SM_TOTAL = SM_BAR + 512 + 2048 + 1024;

constexpr int B_WQ = 0, B_K = 8, B_V = 16, B_WO = 24  , B_WQ2 = 26, B_W1 = 0, B_W3 = 1, B_W2 = 2;
constexpr int B_RSQ = 32, B_QAG = 34, B_RSO = 36, B_RSX = 38, B_RSO2 = 40, B_LS = 41, NBAR = 43;

#define PFMODE 3
#define PF_KB 4096
#define PF_DLY 0
#define KFIRST 1
#define PF_NUM 9
#define PF_DEN 1
#define WO_W -2
#define VMODE 2
#define VPRE_N 2
#define F_DELAY 15000

__device__ u64 g_af[2][CL][NA][64];
__device__ u64 g_fa[2][CL][NF][64];
__device__ unsigned g_epoch;

#define TL(i)
#define TLW(i, w)

struct __align__(64) Maps { CUtensorMap k, v, wq, wq8, wo, w1, w3, w2; };
struct Ptrs { const char *k, *v, *wq, *wo, *w1, *w3, *w2; };

__device__ __forceinline__ void mbar_init(uint32_t a, uint32_t cnt) {
    asm volatile("mbarrier.init.shared.b64 [%0], %1;" ::"r"(a), "r"(cnt) : "memory");
}
__device__ __forceinline__ void mbar_expect(uint32_t a, uint32_t bytes) {
    asm volatile("mbarrier.arrive.expect_tx.shared.b64 _, [%0], %1;" ::"r"(a), "r"(bytes) : "memory");
}
__device__ __forceinline__ void mbar_wait(uint32_t a, uint32_t ph) {
    uint32_t ok; int it = 0;
    do {
        asm volatile("{.reg .pred p; mbarrier.try_wait.parity.shared.b64 p, [%1], %2; selp.u32 %0,1,0,p;}"
                     : "=r"(ok) : "r"(a), "r"(ph) : "memory");
    } while (!ok && ++it < SPIN_LIMIT);
}
__device__ __forceinline__ void mbar_wait_cl(uint32_t a, uint32_t ph) {
    uint32_t ok; int it = 0;
    do {
        asm volatile("{.reg .pred p; mbarrier.try_wait.parity.shared.b64 p, [%1], %2; selp.u32 %0,1,0,p;}"
                     : "=r"(ok) : "r"(a), "r"(ph) : "memory");
    } while (!ok && ++it < SPIN_LIMIT);
}
__device__ __forceinline__ void pin(uint32_t& v) { asm volatile("" : "+r"(v)); }
__device__ __forceinline__ void tma2d(uint32_t dst, const CUtensorMap* m, int c0, int c1, uint32_t bar) {
    asm volatile("cp.async.bulk.tensor.2d.shared::cluster.global.mbarrier::complete_tx::bytes [%0], [%1, {%3, %4}], [%2];"
                 ::"r"(dst), "l"((u64)m), "r"(bar), "r"(c0), "r"(c1) : "memory");
}
__device__ __forceinline__ void tma3d(uint32_t dst, const CUtensorMap* m, int c0, int c1, int c2, uint32_t bar) {
    asm volatile("cp.async.bulk.tensor.3d.shared::cluster.global.mbarrier::complete_tx::bytes [%0], [%1, {%3, %4, %5}], [%2];"
                 ::"r"(dst), "l"((u64)m), "r"(bar), "r"(c0), "r"(c1), "r"(c2) : "memory");
}
__device__ __forceinline__ void tma4d(uint32_t dst, const CUtensorMap* m, int c0, int c1, int c2, int c3, uint32_t bar) {
    asm volatile("cp.async.bulk.tensor.4d.shared::cluster.global.mbarrier::complete_tx::bytes [%0], [%1, {%3, %4, %5, %6}], [%2];"
                 ::"r"(dst), "l"((u64)m), "r"(bar), "r"(c0), "r"(c1), "r"(c2), "r"(c3) : "memory");
}
__device__ __forceinline__ void l2pf(const char* p, uint32_t bytes) {
    asm volatile("cp.async.bulk.prefetch.L2.global [%0], %1;" ::"l"(p), "r"(bytes) : "memory");
}
__device__ __forceinline__ uint32_t mapa(uint32_t a, uint32_t rank) {
    uint32_t r; asm("mapa.shared::cluster.u32 %0, %1, %2;" : "=r"(r) : "r"(a), "r"(rank)); return r;
}
__device__ __forceinline__ void st_async4(uint32_t a, float x, float y, float z, float w, uint32_t bar) {
    asm volatile("st.async.weak.shared::cluster.mbarrier::complete_tx::bytes.v4.f32 [%0], {%1,%2,%3,%4}, [%5];"
                 ::"r"(a), "f"(x), "f"(y), "f"(z), "f"(w), "r"(bar) : "memory");
}
__device__ __forceinline__ void st_async2(uint32_t a, float x, float y, uint32_t bar) {
    asm volatile("st.async.weak.shared::cluster.mbarrier::complete_tx::bytes.v2.f32 [%0], {%1,%2}, [%3];"
                 ::"r"(a), "f"(x), "f"(y), "r"(bar) : "memory");
}
__device__ __forceinline__ void st_async1(uint32_t a, uint32_t x, uint32_t bar) {
    asm volatile("st.async.weak.shared::cluster.mbarrier::complete_tx::bytes.b32 [%0], %1, [%2];"
                 ::"r"(a), "r"(x), "r"(bar) : "memory");
}
__device__ __forceinline__ void ldsm4(uint32_t (&r)[4], uint32_t a) {
    asm volatile("ldmatrix.sync.aligned.m8n8.x4.shared.b16 {%0,%1,%2,%3}, [%4];"
                 : "=r"(r[0]), "=r"(r[1]), "=r"(r[2]), "=r"(r[3]) : "r"(a) : "memory");
}
__device__ __forceinline__ void ldsm4t(uint32_t (&r)[4], uint32_t a) {
    asm volatile("ldmatrix.sync.aligned.m8n8.x4.trans.shared.b16 {%0,%1,%2,%3}, [%4];"
                 : "=r"(r[0]), "=r"(r[1]), "=r"(r[2]), "=r"(r[3]) : "r"(a) : "memory");
}
__device__ __forceinline__ void mma(float (&c)[4], const uint32_t (&a)[4], uint32_t b0, uint32_t b1) {
    asm volatile("mma.sync.aligned.m16n8k16.row.col.f32.bf16.bf16.f32 {%0,%1,%2,%3},{%4,%5,%6,%7},{%8,%9},{%0,%1,%2,%3};"
                 : "+f"(c[0]), "+f"(c[1]), "+f"(c[2]), "+f"(c[3])
                 : "r"(a[0]), "r"(a[1]), "r"(a[2]), "r"(a[3]), "r"(b0), "r"(b1));
}
__device__ __forceinline__ uint4 lds128(uint32_t a) {
    uint4 v; asm volatile("ld.shared.v4.u32 {%0,%1,%2,%3}, [%4];" : "=r"(v.x), "=r"(v.y), "=r"(v.z), "=r"(v.w) : "r"(a) : "memory"); return v;
}
__device__ __forceinline__ float lds32f(uint32_t a) {
    float v; asm volatile("ld.shared.f32 %0, [%1];" : "=f"(v) : "r"(a) : "memory"); return v;
}
__device__ __forceinline__ uint32_t lds32(uint32_t a) {
    uint32_t v; asm volatile("ld.shared.u32 %0, [%1];" : "=r"(v) : "r"(a) : "memory"); return v;
}
__device__ __forceinline__ unsigned short lds16(uint32_t a) {
    unsigned short v; asm volatile("ld.shared.u16 %0, [%1];" : "=h"(v) : "r"(a) : "memory"); return v;
}
__device__ __forceinline__ float2 lds64f(uint32_t a) {
    float2 v; asm volatile("ld.shared.v2.f32 {%0,%1}, [%2];" : "=f"(v.x), "=f"(v.y) : "r"(a) : "memory"); return v;
}
__device__ __forceinline__ void sts16(uint32_t a, unsigned short v) {
    asm volatile("st.shared.u16 [%0], %1;" ::"r"(a), "h"(v) : "memory");
}
__device__ __forceinline__ void sts32(uint32_t a, uint32_t v) {
    asm volatile("st.shared.u32 [%0], %1;" ::"r"(a), "r"(v) : "memory");
}
__device__ __forceinline__ void sts64(uint32_t a, uint32_t x, uint32_t y) {
    asm volatile("st.shared.v2.u32 [%0], {%1,%2};" ::"r"(a), "r"(x), "r"(y) : "memory");
}
__device__ __forceinline__ float ex2(float x) { float y; asm("ex2.approx.ftz.f32 %0, %1;" : "=f"(y) : "f"(x)); return y; }
__device__ __forceinline__ uint32_t pack_bf16(float lo, float hi) {
    uint32_t r; asm("cvt.rn.bf16x2.f32 %0, %1, %2;" : "=r"(r) : "f"(hi), "f"(lo)); return r;
}
__device__ __forceinline__ float bf_lo(uint32_t w) { return __uint_as_float(w << 16); }
__device__ __forceinline__ float bf_hi(uint32_t w) { return __uint_as_float(w & 0xffff0000u); }
__device__ __forceinline__ int f2ord(float x) { int i = __float_as_int(x); return i ^ ((i >> 31) & 0x7fffffff); }
__device__ __forceinline__ float ord2f(int i) { return __int_as_float(i ^ ((i >> 31) & 0x7fffffff)); }
__device__ __forceinline__ void st_pkt(u64* p, float v, unsigned tag) {
    u64 x = ((u64)tag << 32) | __float_as_uint(v);
    asm volatile("st.relaxed.gpu.global.b64 [%0], %1;" ::"l"(p), "l"(x) : "memory");
}
__device__ __forceinline__ u64 ld_pkt(const u64* p) {
    u64 x; asm volatile("ld.relaxed.gpu.global.b64 %0, [%1];" : "=l"(x) : "l"(p) : "memory"); return x;
}
template <int N>
__device__ __forceinline__ float poll_sum(const u64* base, unsigned tag) {
    u64 v[N]; bool ok; int it = 0;
    do {
#pragma unroll
        for (int j = 0; j < N; j++) v[j] = ld_pkt(base + j * 64);
        ok = true;
#pragma unroll
        for (int j = 0; j < N; j++) ok = ok && ((unsigned)(v[j] >> 32) == tag);
    } while (!ok && ++it < SPIN_LIMIT);
    float s[8];
#pragma unroll
    for (int j = 0; j < 8; j++) s[j] = j < N ? __uint_as_float((unsigned)v[j]) : 0.f;
    return ((s[0] + s[1]) + (s[2] + s[3])) + ((s[4] + s[5]) + (s[6] + s[7]));
}

__device__ __forceinline__ int pos2col(int i) { return 16 * (i & 3) + 8 * (i >> 5) + ((i >> 2) & 7); }
__device__ __forceinline__ int kpos64(int k) { return ((k & 7) >> 1) * 16 + (k >> 4) * 4 + ((k >> 3) & 1) * 2 + (k & 1); }
__device__ __forceinline__ int kpos32(int k) { return ((k & 7) >> 1) * 8 + (k >> 4) * 4 + ((k >> 3) & 1) * 2 + (k & 1); }

template <int KT>
__device__ __forceinline__ void load_wfrag(uint32_t (&w)[4][KT][4], uint32_t box, int lane) {
    const int mi = lane >> 3, rr = lane & 7;
    const uint32_t rowa = box + (8 * (mi >> 1) + rr) * 128;
#pragma unroll
    for (int mt = 0; mt < 4; mt++) {
        const uint32_t a = rowa + (((2 * mt + (mi & 1)) ^ rr) << 4);
#pragma unroll
        for (int kt = 0; kt < KT; kt++) ldsm4t(w[mt][kt], a + kt * 2048);
    }
}

template <int KT>
__device__ __forceinline__ void gemv(float (&acc)[4][4], const uint32_t (&w)[4][KT][4], const uint32_t (&b)[2 * KT]) {
#pragma unroll
    for (int mt = 0; mt < 4; mt++) { acc[mt][0] = acc[mt][1] = acc[mt][2] = acc[mt][3] = 0.f; }
#pragma unroll
    for (int kt = 0; kt < KT; kt++)
#pragma unroll
        for (int mt = 0; mt < 4; mt++) mma(acc[mt], w[mt][kt], b[2 * kt], b[2 * kt + 1]);
}
template <bool CS>
__device__ __forceinline__ void gemv_send(const float (&acc)[4][4], int lane, uint32_t dst, uint32_t dbar) {
    const int t = lane & 3;
    float v[4];
#pragma unroll
    for (int mt = 0; mt < 4; mt++) {
        if (CS) v[mt] = (t == 0) ? acc[mt][0] : (t == 1) ? acc[mt][2] : (t == 2) ? acc[mt][1] : acc[mt][3];
        else v[mt] = (t == 0) ? acc[mt][0] : acc[mt][2];
    }
    if (CS || t < 2) st_async4(dst, v[0], v[1], v[2], v[3], dbar);
}

__device__ __forceinline__ float sum8(uint32_t a, int stride) {
    float v[8];
#pragma unroll
    for (int j = 0; j < 8; j++) v[j] = lds32f(a + j * stride);
    return ((v[0] + v[1]) + (v[2] + v[3])) + ((v[4] + v[5]) + (v[6] + v[7]));
}

__device__ __forceinline__ void send_lnstats(const uint32_t (&bx)[8], const uint32_t (&b)[8], int lane, uint32_t dst, uint32_t dbar) {
    float s1[4] = {0.f, 0.f, 0.f, 0.f}, s2[4] = {0.f, 0.f, 0.f, 0.f};
    const uint32_t ones[4] = {0x3f803f80u, 0x3f803f80u, 0x3f803f80u, 0x3f803f80u};
#pragma unroll
    for (int kt = 0; kt < 4; kt++) {
        const uint32_t xa[4] = {bx[2 * kt], bx[2 * kt], bx[2 * kt + 1], bx[2 * kt + 1]};
        mma(s1, ones, b[2 * kt], b[2 * kt + 1]);
        mma(s2, xa, b[2 * kt], b[2 * kt + 1]);
    }
    if ((lane & 3) == 0) st_async2(dst, s1[0], s2[0], dbar);
}
__device__ __forceinline__ void recv_lnstats(uint32_t sb, float& mean, float& rstd) {
    float a1[4], a2[4];
#pragma unroll
    for (int j = 0; j < 4; j++) {
        uint4 v = lds128(sb + SM_LNST + j * 16);
        a1[j] = __uint_as_float(v.x) + __uint_as_float(v.z);
        a2[j] = __uint_as_float(v.y) + __uint_as_float(v.w);
    }
    const float s1 = (a1[0] + a1[1]) + (a1[2] + a1[3]), s2 = (a2[0] + a2[1]) + (a2[2] + a2[3]);
    mean = s1 * (1.f / D_);
    const float var = fmaxf(s2 * (1.f / D_) - mean * mean, 0.f);
    asm("rsqrt.approx.ftz.f32 %0, %1;" : "=f"(rstd) : "f"(var + LN_EPS));
}

struct Ctx {
    uint32_t sb;
    int tid, lane, warp, rank, cid;
    unsigned tag;
    const CUtensorMap* wo;
};

template <bool EXACT, int VPRE, bool WAITV>
__device__ __forceinline__ void attn_pv(const Ctx& c, const float (&sa)[4], const float (&sbv)[4], float rA, float rB,
                                        uint32_t (&vf)[4][8][4], const uint32_t (&va)[4], uint32_t lsbar,
                                        uint32_t rdst, uint32_t sdst, uint32_t rbar) {
    const uint32_t sb = c.sb;
    const int lane = c.lane, warp = c.warp, lg = lane >> 2, lt = lane & 3, hp = lt & 1;
    const int NEG = (int)0x80000000;
    float fA = rA, fB = rB;
    if (EXACT) {
        const int mA = f2ord(fmaxf(fmaxf(sa[0], sa[1]), fmaxf(sa[2], sa[3])));
        const int mB = f2ord(fmaxf(fmaxf(sbv[0], sbv[1]), fmaxf(sbv[2], sbv[3])));
        const int r0 = __reduce_max_sync(~0u, hp == 0 ? mA : NEG);
        const int r1 = __reduce_max_sync(~0u, hp == 0 ? mB : NEG);
        const int r2 = __reduce_max_sync(~0u, hp == 1 ? mA : NEG);
        const int r3 = __reduce_max_sync(~0u, hp == 1 ? mB : NEG);
        const int wA = hp == 0 ? r0 : r2, wB = hp == 0 ? r1 : r3;
        fA = ord2f(wA); fB = ord2f(wB);
        if (lane < 2) sts64(sb + SM_WMAX + lane * 64 + warp * 8, wA, wB);
        __syncwarp();
        if (lane == 0) asm volatile("mbarrier.arrive.shared.b64 _, [%0];" ::"r"(lsbar) : "memory");
    }
    uint32_t b0[4], b1[4];
#pragma unroll
    for (int T = 0; T < 4; T++) {
        const uint32_t pk = pack_bf16(ex2(sa[T] - fA), ex2(sbv[T] - fB));
        asm volatile("movmatrix.sync.aligned.m8n8.trans.b16 %0, %1;" : "=r"(b0[T]) : "r"(pk));
        b1[T] = __shfl_down_sync(~0u, b0[T], 16);
    }
    if (!EXACT) TL(33);
    float oc[8][4], lc[4];
#pragma unroll
    for (int m = 0; m < 8; m++) { oc[m][0] = oc[m][1] = oc[m][2] = oc[m][3] = 0.f; }
    lc[0] = lc[1] = lc[2] = lc[3] = 0.f;
    const uint32_t ones[4] = {0x3f803f80u, 0x3f803f80u, 0x3f803f80u, 0x3f803f80u};
    if (WAITV) {
        mbar_wait(sb + SM_BAR + 8 * (B_V + warp), 0); TL(27);
        if (WO_W >= 0 && c.tid == WO_W * 32) {
            mbar_expect(sb + SM_BAR + 8 * B_WO, 65536);
            tma4d(sb + SM_W, c.wo, 0, 16 * c.rank, 4 * c.cid, 0, sb + SM_BAR + 8 * B_WO);
        }
        __syncwarp();
    }
#pragma unroll
    for (int T = 0; T < 4; T++) {
        if (VPRE == 0) {
#pragma unroll
            for (int m = 0; m < 8; m++) ldsm4t(vf[T][m], va[m & 3] + (m >> 2) * 8192 + T * 2048);
        }
#pragma unroll
        for (int m = 0; m < 8; m++) {
            mma(oc[m], vf[T][m], b0[T], b1[T]);
            if (VPRE > 0 && T + VPRE < 4) ldsm4t(vf[T + VPRE][m], va[m & 3] + (m >> 2) * 8192 + (T + VPRE) * 2048);
        }
        mma(lc, ones, b0[T], b1[T]);
    }
    if (!EXACT) TL(34);
    float gA = 1.f, gB = 1.f;
    if (EXACT) {
        mbar_wait(lsbar, 0);
        int MA = NEG, MB = NEG;
#pragma unroll
        for (int j = 0; j < 4; j++) {
            uint4 v = lds128(sb + SM_WMAX + hp * 64 + j * 16);
            MA = max(MA, max((int)v.x, (int)v.z)); MB = max(MB, max((int)v.y, (int)v.w));
        }
        const float fMA = ord2f(MA), fMB = ord2f(MB);
        gA = ex2(fA - fMA); gB = ex2(fB - fMB);
        fA = fMA; fB = fMB;
    }
    if (lt < 2) {
        const uint32_t pw = sb + SM_PART + warp * PSTR + (lt * 8 + lg) * 16;
#pragma unroll
        for (int m = 0; m < 8; m++) {
            if (EXACT) { oc[m][0] *= gA; oc[m][1] *= gB; oc[m][2] *= gA; oc[m][3] *= gB; }
            asm volatile("st.shared.v4.f32 [%0], {%1,%2,%3,%4};" ::"r"(pw + m * 256), "f"(oc[m][0]), "f"(oc[m][1]),
                         "f"(oc[m][2]), "f"(oc[m][3]) : "memory");
        }
        if (lg == 0) sts64(sb + SM_PART + warp * PSTR + 2048 + lt * 8, __float_as_uint(lc[0] * gA), __float_as_uint(lc[1] * gB));
    }
    if (!EXACT) TL(36);
    __syncthreads();
    float2 v[8], u[8];
#pragma unroll
    for (int w = 0; w < 8; w++) v[w] = lds64f(sb + SM_PART + c.tid * 8 + w * PSTR);
    if (lane < 2) {
#pragma unroll
        for (int w = 0; w < 8; w++) u[w] = lds64f(sb + SM_PART + w * PSTR + 2048 + lane * 8);
    }
    st_async2(rdst, ((v[0].x + v[1].x) + (v[2].x + v[3].x)) + ((v[4].x + v[5].x) + (v[6].x + v[7].x)),
              ((v[0].y + v[1].y) + (v[2].y + v[3].y)) + ((v[4].y + v[5].y) + (v[6].y + v[7].y)), rbar);
    if (lane < 2)
        st_async4(sdst, fA, ((u[0].x + u[1].x) + (u[2].x + u[3].x)) + ((u[4].x + u[5].x) + (u[6].x + u[7].x)),
                  fB, ((u[0].y + u[1].y) + (u[2].y + u[3].y)) + ((u[4].y + u[5].y) + (u[6].y + u[7].y)), rbar);
}

__device__ __forceinline__ float combine_exact(uint32_t sta, uint32_t ra, float& M) {
    float2 st[8]; float pv[8];
#pragma unroll
    for (int s = 0; s < 8; s++) st[s] = lds64f(sta + s * 32);
#pragma unroll
    for (int s = 0; s < 8; s++) pv[s] = lds32f(ra + s * 256);
    M = fmaxf(fmaxf(fmaxf(st[0].x, st[1].x), fmaxf(st[2].x, st[3].x)), fmaxf(fmaxf(st[4].x, st[5].x), fmaxf(st[6].x, st[7].x)));
    float f[8];
#pragma unroll
    for (int s = 0; s < 8; s++) f[s] = ex2(st[s].x - M);
    const float num = ((f[0] * pv[0] + f[1] * pv[1]) + (f[2] * pv[2] + f[3] * pv[3])) + ((f[4] * pv[4] + f[5] * pv[5]) + (f[6] * pv[6] + f[7] * pv[7]));
    const float den = ((f[0] * st[0].y + f[1] * st[1].y) + (f[2] * st[2].y + f[3] * st[3].y)) + ((f[4] * st[4].y + f[5] * st[5].y) + (f[6] * st[6].y + f[7] * st[7].y));
    return __fdividef(num, den);
}

__device__ __noinline__ void attn_redo(uint32_t sb, float a0, float a1, float a2, float a3, float b0, float b1, float b2, float b3) {
    Ctx c;
    c.sb = sb; c.tid = threadIdx.x; c.lane = c.tid & 31; c.warp = c.tid >> 5;
    c.rank = blockIdx.x % CL; c.cid = blockIdx.x / CL; c.tag = 0; c.wo = nullptr;
    const int lane = c.lane, warp = c.warp, tid = c.tid, rank = c.rank;
    const uint32_t bar = sb + SM_BAR;
    const float sa[4] = {a0, a1, a2, a3}, sbv[4] = {b0, b1, b2, b3};
    uint32_t vf[4][8][4], va[4];
    const int mi = lane >> 3, rr = lane & 7;
#pragma unroll
    for (int m = 0; m < 4; m++)
        va[m] = sb + SM_KV + warp * 16384 + (8 * (mi >> 1) + rr) * 128 + (((2 * m + (mi & 1)) ^ rr) << 4);
    attn_pv<true, 0, false>(c, sa, sbv, 0.f, 0.f, vf, va, bar + 8 * (B_LS + 1),
                            mapa(sb + SM_RS0 + rank * 256 + lane * 8, warp),
                            mapa(sb + SM_RS0 + 2048 + rank * 32 + (lane & 1) * 16, warp), mapa(bar + 8 * B_RSO2, warp));
    if (warp < 2) {
        const int j = tid & 3, head = 2 * (tid >> 5) + (j & 1), dd = ((tid >> 2) & 7) + 8 * (j >> 1);
        mbar_wait_cl(bar + 8 * B_RSO2, 0);
        float M;
        const float o = combine_exact(sb + SM_RS0 + 2048 + head * 8, sb + SM_RS0 + tid * 4, M);
        sts16(sb + SM_XB1 + 2 * kpos64(head * 16 + dd), __bfloat16_as_ushort(__float2bfloat16(o)));
    }
    __syncthreads();
}

template <int L>
__device__ __forceinline__ void attn_layer(const Ctx& c, const Maps& mp, unsigned short x0raw,
                                           uint32_t (&kf)[4][8][4], float& cs) {
    const uint32_t sb = c.sb;
    const int lane = c.lane, warp = c.warp, tid = c.tid, rank = c.rank, g = c.cid;
    const int lg = lane >> 2, lt = lane & 3;
    const uint32_t bar = sb + SM_BAR;
    const uint32_t wbox = sb + SM_W + warp * 8192;

    if (L == 0) {
        const uint32_t kb = sb + SM_KV + warp * 16384;
        mbar_wait(bar + 8 * (B_K + warp), 0);
        TLW(25, 0); TLW(26, 7);
        const int mi = lane >> 3, rr = lane & 7;
#pragma unroll
        for (int T = 0; T < 4; T++) {
            const int x7 = rr;
            const uint32_t rowa = kb + (16 * T + 8 * (mi & 1) + x7) * 128;
#pragma unroll
            for (int s = 0; s < 8; s++)
                ldsm4(kf[T][s], rowa + (s >> 2) * 8192 + (((2 * (s & 3) + (mi >> 1)) ^ x7) << 4));
        }
        __syncwarp();
        if (lane == 0) {
            const int row = g * SK_ + (SK_ - WIN_) + rank * 512 + warp * 64;
            mbar_expect(bar + 8 * (B_V + warp), 16384);
            tma3d(kb, &mp.v, 0, row, 0, bar + 8 * (B_V + warp));
            if (warp == 7 && WO_W == -1) {
                mbar_expect(bar + 8 * B_WO, 65536);
                tma4d(sb + SM_W, &mp.wo, 0, 16 * rank, 4 * g, 0, bar + 8 * B_WO);
            }
        }
    }
    {
        uint32_t wf[4][4][4];
        mbar_wait(bar + 8 * (L == 0 ? B_WQ + warp : B_WQ2), 0);
        load_wfrag<4>(wf, wbox, lane);
        uint32_t xa = sb + SM_XB0 + 2 * kpos64(pos2col(tid & 63));
        uint32_t dst = mapa(sb + SM_RS0 + rank * 512 + lt * 128 + lg * 16, warp), dbar = mapa(bar + 8 * (B_RSQ + L), warp);
        uint32_t ba = sb + SM_XB0 + lt * 32;
        uint32_t sdst = mapa(sb + SM_LNST + rank * 8, lg), sbar = mapa(bar + 8 * (B_RSQ + L), lg);
        pin(xa); pin(dst); pin(dbar); pin(ba); pin(sdst); pin(sbar);
        TL(L * 12 + 1);
        if (warp < 2) {
            unsigned short xb = x0raw;
            if (L == 1) xb = __bfloat16_as_ushort(__float2bfloat16(poll_sum<NF>(&g_fa[0][rank][0][tid], c.tag)));
            sts16(xa, xb);
        }
        TL(L * 12 + 2);
        __syncthreads();
        uint32_t bx[8], b[8];
        {
            uint4 v0 = lds128(ba), v1 = lds128(ba + 16);
            bx[0] = v0.x; bx[1] = v0.y; bx[2] = v0.z; bx[3] = v0.w; bx[4] = v1.x; bx[5] = v1.y; bx[6] = v1.z; bx[7] = v1.w;
#pragma unroll
            for (int j = 0; j < 8; j++) b[j] = (L == 0 && (lg == 5 || lg == 7)) ? 0x3f803f80u : bx[j];
        }
        if (warp == 7) send_lnstats(bx, b, lane, sdst, sbar);
        float acc[4][4];
        gemv<4>(acc, wf, b);
        gemv_send<L == 0>(acc, lane, dst, dbar);
        if ((L == 1 || WO_W == -2) && tid == 64) {
            mbar_expect(bar + 8 * (B_WO + L), 65536);
            tma4d(sb + SM_W, &mp.wo, 0, 16 * rank, 4 * g, 0, bar + 8 * (B_WO + L));
        }
    }
    TL(L * 12 + 3);
    constexpr int VPRE = (L == 1) ? VPRE_N : 0;
    uint32_t vf[4][8][4];
    uint32_t va[4];
    {
        const int mi = lane >> 3, rr = lane & 7;
#pragma unroll
        for (int m = 0; m < 4; m++)
            va[m] = sb + SM_KV + warp * 16384 + (8 * (mi >> 1) + rr) * 128 + (((2 * m + (mi & 1)) ^ rr) << 4);
    }
    if (warp < 2) {
        const bool odd = (tid >> 2) & 1;
        const int d = 64 * (rank & 1) + pos2col(tid);
        const int p = d >> 1, s = p >> 3;
        const uint32_t a = sb + SM_QB + (rank >> 1) * 320 + ((s >> 1) * 16 + (p & 3) * 4 + (s & 1) * 2 + ((p >> 2) & 1)) * 4;
        uint32_t da[4], db[4];
#pragma unroll
        for (int j = 0; j < 4; j++) {
            da[j] = mapa(a, (odd ? 4 : 0) + j); db[j] = mapa(bar + 8 * (B_QAG + L), (odd ? 4 : 0) + j);
            pin(da[j]); pin(db[j]);
        }
        uint32_t ra = sb + SM_RS0 + tid * 4;
        pin(ra);
        mbar_wait_cl(bar + 8 * (B_RSQ + L), 0);
        const float v = sum8(ra, 512);
        if (L == 0) cs = sum8(ra + 256, 512);
        float mean, rstd;
        recv_lnstats(sb, mean, rstd);
        const float q = (v - mean * cs) * (rstd * QSCALE);
        const float qo = __shfl_xor_sync(~0u, q, 4);
        const uint32_t word = odd ? pack_bf16(qo, q) : pack_bf16(q, qo);
#pragma unroll
        for (int j = 0; j < 4; j++) st_async1(da[j], word, db[j]);
    }
    __syncwarp();
#pragma unroll
    for (int T = 0; T < VPRE; T++)
#pragma unroll
        for (int m = 0; m < 8; m++) ldsm4t(vf[T][m], va[m & 3] + (m >> 2) * 8192 + T * 2048);
    TL(L * 12 + 4);
    float sa[4], sbv[4];
    {
        const int hp = lt & 1;
        uint32_t qa = sb + SM_QB + (lg & 3) * 320 + lt * 16;
        uint32_t rdst = mapa(sb + SM_RS1 + rank * 256 + lane * 8, warp), rbar = mapa(bar + 8 * (B_RSO + L), warp);
        uint32_t sdst = mapa(sb + SM_OST + rank * 32 + hp * 16, warp);
        float2 ref = make_float2(0.f, 0.f);
        if (L == 1) ref = lds64f(sb + SM_MREF + hp * 8);
        pin(qa); pin(rdst); pin(rbar); pin(sdst);
        mbar_wait_cl(bar + 8 * (B_QAG + L), 0);
        TL(L * 12 + 5);
        uint32_t qb[16];
#pragma unroll
        for (int i = 0; i < 4; i++) {
            uint4 v = lds128(qa + i * 64);
            qb[4 * i] = v.x; qb[4 * i + 1] = v.y; qb[4 * i + 2] = v.z; qb[4 * i + 3] = v.w;
        }
        float sc[4][4];
#pragma unroll
        for (int T = 0; T < 4; T++) { sc[T][0] = sc[T][1] = sc[T][2] = sc[T][3] = 0.f; }
#pragma unroll
        for (int s = 0; s < 8; s++)
#pragma unroll
            for (int T = 0; T < 4; T++) mma(sc[T], kf[T][s], qb[2 * s], qb[2 * s + 1]);
        if (L == 1) TL(32);
#pragma unroll
        for (int T = 0; T < 4; T++) { sa[T] = (lt < 2) ? sc[T][0] : sc[T][2]; sbv[T] = (lt < 2) ? sc[T][1] : sc[T][3]; }
        attn_pv<L == 0, VPRE, L == 0>(c, sa, sbv, ref.x, ref.y, vf, va, bar + 8 * B_LS, rdst, sdst, rbar);
    }
    TL(L * 12 + 7);
    {
        uint32_t wf[4][4][4];
        uint32_t dst = mapa(sb + SM_RS2 + rank * 256 + lt * 128 + lg * 16, warp), dbar = mapa(bar + 8 * (B_RSX + L), warp);
        uint32_t ba = sb + SM_XB1 + lt * 32;
        pin(dst); pin(dbar); pin(ba);
        const int j = tid & 3, head = 2 * (tid >> 5) + (j & 1), dd = ((tid >> 2) & 7) + 8 * (j >> 1);
        uint32_t xa = sb + SM_XB1 + 2 * kpos64((head * 16 + dd) & 63);
        if (warp >= 2) {
            mbar_wait(bar + 8 * (B_WO + L), 0);
            if (L == 0) TLW(29, 7);
            load_wfrag<4>(wf, wbox, lane);
        } else {
            uint32_t sta = sb + SM_OST + head * 8, ra = sb + SM_RS1 + tid * 4;
            pin(sta); pin(ra); pin(xa);
            if (L == 1) { mbar_wait(bar + 8 * (B_WO + L), 0); load_wfrag<4>(wf, wbox, lane); }
            mbar_wait_cl(bar + 8 * (B_RSO + L), 0);
            TL(L * 12 + 8);
            if (L == 0) {
                float M;
                const float o = combine_exact(sta, ra, M);
                sts16(xa, __bfloat16_as_ushort(__float2bfloat16(o)));
                if (lane < 2) sts32(sb + SM_MREF + head * 4, __float_as_uint(M));
                mbar_wait(bar + 8 * (B_WO + L), 0); load_wfrag<4>(wf, wbox, lane);
            } else {
                const float den = sum8(sta + 4, 32), num = sum8(ra, 256);
                sts16(xa, __bfloat16_as_ushort(__float2bfloat16(__fdividef(num, den))));
                const bool bad = !(den >= 5.4e-20f && den <= 1.8e19f);
                const unsigned anyb = __ballot_sync(~0u, bad);
                if (lane == 0) sts32(sb + SM_FLAG + warp * 4, anyb);
            }
        }
        __syncthreads();
        uint4 v0 = lds128(ba), v1 = lds128(ba + 16);
        if (L == 1) {
            const float2 fl = lds64f(sb + SM_FLAG);
            if (__builtin_expect((__float_as_uint(fl.x) | __float_as_uint(fl.y)) != 0, 0)) {
                attn_redo(sb, sa[0], sa[1], sa[2], sa[3], sbv[0], sbv[1], sbv[2], sbv[3]);
                load_wfrag<4>(wf, wbox, lane);
                v0 = lds128(ba); v1 = lds128(ba + 16);
            }
        }
        uint32_t b[8];
        b[0] = v0.x; b[1] = v0.y; b[2] = v0.z; b[3] = v0.w; b[4] = v1.x; b[5] = v1.y; b[6] = v1.z; b[7] = v1.w;
        float acc[4][4];
        gemv<4>(acc, wf, b);
        gemv_send<false>(acc, lane, dst, dbar);
        if (L == 0 && tid == 64) {
            mbar_expect(bar + 8 * B_WQ2, 65536);
            tma3d(sb + SM_W, &mp.wq8, 0, 64 * rank, 8 * g, bar + 8 * B_WQ2);
        }
    }
    TL(L * 12 + 9);
    if (warp < 2) {
        float xres = 0.f;
        if (g == 0) xres = __uint_as_float((uint32_t)lds16(sb + SM_XB0 + 2 * kpos64(pos2col(tid))) << 16);
        u64* gp = &g_af[L][rank][g][tid];
        uint32_t ra = sb + SM_RS2 + tid * 4;
        asm volatile("" : "+l"(gp), "+f"(xres)); pin(ra);
        mbar_wait_cl(bar + 8 * (B_RSX + L), 0);
        st_pkt(gp, sum8(ra, 256) + xres, c.tag);
    }
    TL(L * 12 + 10);
}

template <int L>
__device__ __forceinline__ void ffn_layer(const Ctx& c, uint32_t (&w13)[4][4][4], uint32_t (&w2)[4][2][4], float& cs) {
    const uint32_t sb = c.sb;
    const int lane = c.lane, warp = c.warp, tid = c.tid, rank = c.rank, fc = c.cid - NA;
    const int lg = lane >> 2, lt = lane & 3;
    const uint32_t bar = sb + SM_BAR;
    if (L == 0) {
        const int mi = lane >> 3, rr = lane & 7;
        mbar_wait(bar + 8 * B_W1, 0);
        mbar_wait(bar + 8 * B_W3, 0);
#pragma unroll
        for (int mt = 0; mt < 4; mt++) {
            const uint32_t box = sb + (mt < 2 ? SM_W1 : SM_W3) + (warp >> 1) * 8192;
            const uint32_t a = box + (8 * (mi >> 1) + rr) * 128 + (((4 * (warp & 1) + 2 * (mt & 1) + (mi & 1)) ^ rr) << 4);
#pragma unroll
            for (int kt = 0; kt < 4; kt++) ldsm4t(w13[mt][kt], a + kt * 2048);
        }
    }
    {
        uint32_t xa = sb + SM_XB0 + 2 * kpos64(pos2col(tid & 63));
        uint32_t dst = mapa(sb + SM_RS0 + rank * 512 + lt * 128 + lg * 16, warp), dbar = mapa(bar + 8 * (B_RSQ + L), warp);
        uint32_t ba = sb + SM_XB0 + lt * 32;
        uint32_t sdst = mapa(sb + SM_LNST + rank * 8, lg), sbar = mapa(bar + 8 * (B_RSQ + L), lg);
        pin(xa); pin(dst); pin(dbar); pin(ba); pin(sdst); pin(sbar);
        TL(L * 12 + 1);
        if (warp < 2) sts16(xa, __bfloat16_as_ushort(__float2bfloat16(poll_sum<NA>(&g_af[L][rank][0][tid], c.tag))));
        TL(L * 12 + 2);
        __syncthreads();
        uint32_t bx[8], b[8];
        {
            uint4 v0 = lds128(ba), v1 = lds128(ba + 16);
            bx[0] = v0.x; bx[1] = v0.y; bx[2] = v0.z; bx[3] = v0.w; bx[4] = v1.x; bx[5] = v1.y; bx[6] = v1.z; bx[7] = v1.w;
#pragma unroll
            for (int j = 0; j < 8; j++) b[j] = (L == 0 && (lg == 5 || lg == 7)) ? 0x3f803f80u : bx[j];
        }
        if (warp == 7) send_lnstats(bx, b, lane, sdst, sbar);
        float acc[4][4];
        gemv<4>(acc, w13, b);
        gemv_send<L == 0>(acc, lane, dst, dbar);
    }
    TL(L * 12 + 3);
    {
        uint32_t dst = mapa(sb + SM_RS2 + rank * 256 + lt * 128 + lg * 16, warp), dbar = mapa(bar + 8 * (B_RSX + L), warp);
        uint32_t ba = sb + SM_XB1 + lt * 16;
        pin(dst); pin(dbar); pin(ba);
        if (L == 0 && warp >= 2) {
            mbar_wait(bar + 8 * B_W2, 0);
            load_wfrag<2>(w2, sb + SM_W2 + warp * 4096, lane);
        }
        TL(L * 12 + 4);
        if (warp < 2) {
            const int hidx = 16 * (tid & 1) + 8 * (tid >> 5) + ((tid >> 2) & 7);
            uint32_t ra = sb + SM_RS0 + tid * 4, xa = sb + SM_XB1 + 2 * kpos32(hidx);
            pin(ra); pin(xa);
            mbar_wait_cl(bar + 8 * (B_RSQ + L), 0);
            TL(L * 12 + 5);
            const float v = sum8(ra, 512);
            if (L == 0) cs = sum8(ra + 256, 512);
            float mean, rstd;
            recv_lnstats(sb, mean, rstd);
            const float y = (v - mean * cs) * rstd;
            const float yo = __shfl_xor_sync(~0u, y, 2);
            const float h = __fdividef(y, 1.f + ex2(-1.4426950408889634f * y)) * yo;
            if ((tid & 2) == 0) sts16(xa, __bfloat16_as_ushort(__float2bfloat16(h)));
            if (L == 0) {
                mbar_wait(bar + 8 * B_W2, 0);
                load_wfrag<2>(w2, sb + SM_W2 + warp * 4096, lane);
            }
        }
        __syncthreads();
        uint32_t b[4];
        uint4 v0 = lds128(ba);
        b[0] = v0.x; b[1] = v0.y; b[2] = v0.z; b[3] = v0.w;
        float acc[4][4];
        gemv<2>(acc, w2, b);
        gemv_send<false>(acc, lane, dst, dbar);
    }
    TL(L * 12 + 6);
    if (warp < 2) {
        float xres = 0.f;
        if (fc == 0) xres = __uint_as_float((uint32_t)lds16(sb + SM_XB0 + 2 * kpos64(pos2col(tid))) << 16);
        u64* gp = &g_fa[L][rank][fc][tid];
        uint32_t ra = sb + SM_RS2 + tid * 4;
        asm volatile("" : "+l"(gp), "+f"(xres)); pin(ra);
        mbar_wait_cl(bar + 8 * (B_RSX + L), 0);
        st_pkt(gp, sum8(ra, 256) + xres, c.tag);
    }
    TL(L * 12 + 7);
}

__global__ void __launch_bounds__(NT, 1)
fused_kernel(const __grid_constant__ Maps mp, const Ptrs pt, const bf16* __restrict__ xin, bf16* __restrict__ out) {
    extern __shared__ unsigned char smem_raw[];
    Ctx c;
    c.sb = ((uint32_t)__cvta_generic_to_shared(smem_raw) + 1023u) & ~1023u;
    c.tid = threadIdx.x; c.lane = c.tid & 31; c.warp = c.tid >> 5;
    c.rank = blockIdx.x % CL; c.cid = blockIdx.x / CL;
    const uint32_t sb = c.sb, bar = sb + SM_BAR;
    c.wo = &mp.wo;
    const bool isA = c.cid < NA;
    const long long t0 = clock64();
    unsigned ep; asm volatile("ld.relaxed.gpu.global.u32 %0, [%1];" : "=r"(ep) : "l"(&g_epoch) : "memory");
    unsigned short x0raw = 0;
    if (isA && c.tid < 64) asm volatile("ld.global.nc.u16 %0, [%1];" : "=h"(x0raw) : "l"(xin + 64 * c.rank + pos2col(c.tid)) : "memory");
    if (isA) {
        const int g = c.cid, r = c.rank, l = c.lane, w = c.warp;
        if (c.tid == 255) {
            asm volatile("prefetch.tensormap [%0];" ::"l"((u64)&mp.wq) : "memory");
            asm volatile("prefetch.tensormap [%0];" ::"l"((u64)&mp.k) : "memory");
        }
        if (PF_DLY > 0) while (clock64() - t0 < PF_DLY) {}
        if (!KFIRST && l >= 8 && l < 16) l2pf(pt.wq + (size_t)(64 * r + 8 * w + l - 8) * 8192 + g * 1024, 1024);
        if (l == 16) l2pf(pt.k + ((size_t)g * SK_ + (SK_ - WIN_) + r * 512 + w * 64) * 256, PF_KB);
    }
    if (c.lane == 0) {
        if (isA) {
            const int g = c.cid, w = c.warp;
            mbar_init(bar + 8 * (B_WQ + w), 1);
            mbar_init(bar + 8 * (B_K + w), 1);
            asm volatile("fence.mbarrier_init.release.cluster;" ::: "memory");
            mbar_expect(bar + 8 * (B_K + w), 16384);
            tma3d(sb + SM_KV + w * 16384, &mp.k, 0, g * SK_ + (SK_ - WIN_) + c.rank * 512 + w * 64, 0, bar + 8 * (B_K + w));
            mbar_expect(bar + 8 * (B_WQ + w), 8192);
            tma2d(sb + SM_W + w * 8192, &mp.wq, 512 * g + 64 * w, 64 * c.rank, bar + 8 * (B_WQ + w));
        }
    } else if (c.lane <= 6) {
        const int i = c.warp * 6 + c.lane - 1;
        if (i < NBAR && !(isA && i < 16)) {
            mbar_init(bar + 8 * i, i >= B_LS ? 8 : 1);
            asm volatile("fence.mbarrier_init.release.cluster;" ::: "memory");
            if (i >= B_RSQ && i < B_LS) {
                const uint32_t bytes = (i == B_RSQ) ? 4160 : (i == B_RSQ + 1) ? 2112 : (i < B_RSO) ? 1024 : (i < B_RSX || i == B_RSO2) ? 2304 : 2048;
                mbar_expect(bar + 8 * i, bytes);
            }
        }
    } else if (c.lane == 7 && c.warp < 3) {
        const CUtensorMap* m = isA ? (c.warp == 0 ? &mp.wq8 : c.warp == 1 ? &mp.v : &mp.wo)
                                   : (c.warp == 0 ? &mp.w1 : c.warp == 1 ? &mp.w3 : &mp.w2);
        asm volatile("prefetch.tensormap [%0];" ::"l"((u64)m) : "memory");
    }
    TL(11);
    __syncthreads();
    TL(12);
    asm volatile("barrier.cluster.arrive.relaxed.aligned;" ::: "memory");
    c.tag = ep + 1;
    asm volatile("barrier.cluster.wait.aligned;" ::: "memory");
    TL(23);

    if (isA) {
        uint32_t kf[4][8][4];
        float cs = 0.f;
        attn_layer<0>(c, mp, x0raw, kf, cs);
        attn_layer<1>(c, mp, x0raw, kf, cs);
        if (c.cid == 0 && c.tid < 64) {
            bf16* op = out + 64 * c.rank + pos2col(c.tid);
            asm volatile("" : "+l"(op));
            *op = __float2bfloat16(poll_sum<NF>(&g_fa[1][c.rank][0][c.tid], c.tag));
            if (c.rank == 0 && c.tid == 0)
                asm volatile("st.relaxed.gpu.global.u32 [%0], %1;" ::"l"(&g_epoch), "r"(c.tag) : "memory");
        }
        TL(24);
    } else {
        const int fc = c.cid - NA;
        uint32_t w13[4][4][4], w2[4][2][4];
        float cs = 0.f;
        if (c.tid == 0) {
            while (clock64() - t0 < F_DELAY) {}
            mbar_expect(bar + 8 * B_W1, 32768);
            tma3d(sb + SM_W1, &mp.w1, 0, 64 * c.rank, 4 * fc, bar + 8 * B_W1);
            mbar_expect(bar + 8 * B_W3, 32768);
            tma3d(sb + SM_W3, &mp.w3, 0, 64 * c.rank, 4 * fc, bar + 8 * B_W3);
            mbar_expect(bar + 8 * B_W2, 32768);
            tma3d(sb + SM_W2, &mp.w2, 0, 256 * fc + 32 * c.rank, 0, bar + 8 * B_W2);
        }
        __syncwarp();
        ffn_layer<0>(c, w13, w2, cs);
        ffn_layer<1>(c, w13, w2, cs);
    }
}

__device__ float fb_x[2][D_], fb_q[4096], fb_o[4096], fb_h[FF_];
__device__ float fb_part[32][16][DH_ + 2];

__device__ __forceinline__ void fb_ln(const float* x, float* xn, float* red) {
    const int t = threadIdx.x;
    float a = x[t], b = x[t + 256];
    float s = a + b;
    for (int o = 16; o; o >>= 1) s += __shfl_xor_sync(~0u, s, o);
    if ((t & 31) == 0) red[t >> 5] = s;
    __syncthreads();
    float m = 0.f; for (int i = 0; i < 8; i++) m += red[i];
    m *= (1.f / D_);
    __syncthreads();
    float v = (a - m) * (a - m) + (b - m) * (b - m);
    for (int o = 16; o; o >>= 1) v += __shfl_xor_sync(~0u, v, o);
    if ((t & 31) == 0) red[t >> 5] = v;
    __syncthreads();
    float var = 0.f; for (int i = 0; i < 8; i++) var += red[i];
    const float r = rsqrtf(var * (1.f / D_) + LN_EPS);
    xn[t] = (a - m) * r; xn[t + 256] = (b - m) * r;
    __syncthreads();
}
__global__ void fb_init(const bf16* x) { fb_x[0][threadIdx.x] = __bfloat162float(x[threadIdx.x]); }
__global__ void fb_qk(const bf16* wq) {
    __shared__ float xn[D_], red[8], part[8][32];
    fb_ln(fb_x[0], xn, red);
    const int col = blockIdx.x * 32 + (threadIdx.x & 31), kg = threadIdx.x >> 5;
    float s = 0.f;
    for (int k = kg * 64; k < kg * 64 + 64; k++) s += xn[k] * __bfloat162float(wq[(size_t)k * 4096 + col]);
    part[kg][threadIdx.x & 31] = s;
    __syncthreads();
    if (threadIdx.x < 32) { float v = 0.f; for (int i = 0; i < 8; i++) v += part[i][threadIdx.x]; fb_q[col] = v * QSCALE; }
}
__global__ void fb_attn(const bf16* kc, const bf16* vc) {
    __shared__ float q[DH_], p[256], red[8];
    const int h = blockIdx.x, sp = blockIdx.y, t = threadIdx.x;
    if (t < DH_) q[t] = fb_q[h * DH_ + t];
    __syncthreads();
    const size_t row0 = (size_t)(h / 4) * SK_ + (SK_ - WIN_) + sp * 256;
    const bf16* kr = kc + (row0 + t) * DH_;
    float s = 0.f;
    for (int d = 0; d < DH_; d++) s += q[d] * __bfloat162float(kr[d]);
    float m = s;
    for (int o = 16; o; o >>= 1) m = fmaxf(m, __shfl_xor_sync(~0u, m, o));
    if ((t & 31) == 0) red[t >> 5] = m;
    __syncthreads();
    m = red[0]; for (int i = 1; i < 8; i++) m = fmaxf(m, red[i]);
    const float e = exp2f(s - m);
    p[t] = e;
    __syncthreads();
    if (t < DH_) {
        float o = 0.f, l = 0.f;
        for (int k = 0; k < 256; k++) { o += p[k] * __bfloat162float(vc[(row0 + k) * DH_ + t]); l += p[k]; }
        fb_part[h][sp][t] = o;
        if (t == 0) { fb_part[h][sp][DH_] = m; fb_part[h][sp][DH_ + 1] = l; }
    }
}
__global__ void fb_comb() {
    const int h = blockIdx.x, t = threadIdx.x;
    float M = fb_part[h][0][DH_];
    for (int s = 1; s < 16; s++) M = fmaxf(M, fb_part[h][s][DH_]);
    float num = 0.f, den = 0.f;
    for (int s = 0; s < 16; s++) { const float f = exp2f(fb_part[h][s][DH_] - M); num += f * fb_part[h][s][t]; den += f * fb_part[h][s][DH_ + 1]; }
    fb_o[h * DH_ + t] = num / den;
}
__global__ void fb_proj(const bf16* W, int K, int which, bf16* out) {
    __shared__ float part[32][33];
    const float* v = which == 0 ? fb_o : fb_h;
    const int col = blockIdx.x * 32 + (threadIdx.x & 31), kg = threadIdx.x >> 5;
    float s = 0.f;
    for (int k = kg; k < K; k += 32) s += v[k] * __bfloat162float(W[(size_t)k * D_ + col]);
    part[kg][threadIdx.x & 31] = s;
    __syncthreads();
    if (threadIdx.x < 32) {
        float y = fb_x[which][col];
        for (int i = 0; i < 32; i++) y += part[i][threadIdx.x];
        const bf16 yb = __float2bfloat16(y);
        fb_x[which ^ 1][col] = __bfloat162float(yb);
        if (out) out[col] = yb;
    }
}
__global__ void fb_ffn1(const bf16* w1, const bf16* w3) {
    __shared__ float xn[D_], red[8], pg[8][32], pu[8][32];
    fb_ln(fb_x[1], xn, red);
    const int col = blockIdx.x * 32 + (threadIdx.x & 31), kg = threadIdx.x >> 5;
    float a = 0.f, b = 0.f;
    for (int k = kg * 64; k < kg * 64 + 64; k++) {
        a += xn[k] * __bfloat162float(w1[(size_t)k * FF_ + col]);
        b += xn[k] * __bfloat162float(w3[(size_t)k * FF_ + col]);
    }
    pg[kg][threadIdx.x & 31] = a; pu[kg][threadIdx.x & 31] = b;
    __syncthreads();
    if (threadIdx.x < 32) {
        float gt = 0.f, up = 0.f;
        for (int i = 0; i < 8; i++) { gt += pg[i][threadIdx.x]; up += pu[i][threadIdx.x]; }
        fb_h[col] = gt / (1.f + __expf(-gt)) * up;
    }
}

typedef CUresult (*EncodeFn)(CUtensorMap*, CUtensorMapDataType, cuuint32_t, void*, const cuuint64_t*, const cuuint64_t*,
                             const cuuint32_t*, const cuuint32_t*, CUtensorMapInterleave, CUtensorMapSwizzle,
                             CUtensorMapL2promotion, CUtensorMapFloatOOBfill);

bool make_map(EncodeFn enc, CUtensorMap* m, const void* p, int rank, const cuuint64_t* dims, const cuuint64_t* strides,
              const cuuint32_t* box) {
    const cuuint32_t es[4] = {1, 1, 1, 1};
    return enc(m, CU_TENSOR_MAP_DATA_TYPE_BFLOAT16, rank, const_cast<void*>(p), dims, strides, box, es,
               CU_TENSOR_MAP_INTERLEAVE_NONE, CU_TENSOR_MAP_SWIZZLE_128B, CU_TENSOR_MAP_L2_PROMOTION_L2_256B,
               CU_TENSOR_MAP_FLOAT_OOB_FILL_NONE) == CUDA_SUCCESS;
}

}

extern "C" void kernel_launch(void* const* d_in, const int* in_sizes, int n_in, void* d_out, int out_size) {
    const bf16* x = (const bf16*)d_in[0];
    const bf16* kc = (const bf16*)d_in[1];
    const bf16* vc = (const bf16*)d_in[2];
    const bf16* wq = (const bf16*)d_in[3];
    const bf16* wo = (const bf16*)d_in[4];
    const bf16* w1 = (const bf16*)d_in[6];
    const bf16* w3 = (const bf16*)d_in[7];
    const bf16* w2 = (const bf16*)d_in[8];
    bf16* out = (bf16*)d_out;
    cudaStream_t st = cudaStreamPerThread;

    cudaLaunchConfig_t cfg = {};
    cfg.gridDim = dim3((NA + NF) * CL); cfg.blockDim = dim3(NT); cfg.dynamicSmemBytes = SM_TOTAL; cfg.stream = st;
    cudaLaunchAttribute at[1];
    at[0].id = cudaLaunchAttributeClusterDimension;
    at[0].val.clusterDim.x = CL; at[0].val.clusterDim.y = 1; at[0].val.clusterDim.z = 1;
    cfg.attrs = at; cfg.numAttrs = 1;

    static int mode = -1;
    static EncodeFn enc = nullptr;
    if (mode < 0) {
        mode = 0;
        void* fn = nullptr;
        cudaDriverEntryPointQueryResult qr;
        int ncl = 0;
        if (cudaFuncSetAttribute(fused_kernel, cudaFuncAttributeMaxDynamicSharedMemorySize, SM_TOTAL) == cudaSuccess &&
            cudaOccupancyMaxActiveClusters(&ncl, fused_kernel, &cfg) == cudaSuccess && ncl >= NA + NF &&
            cudaGetDriverEntryPoint("cuTensorMapEncodeTiled", &fn, cudaEnableDefault, &qr) == cudaSuccess && fn) {
            enc = (EncodeFn)fn;
            mode = 1;
        }
        (void)cudaGetLastError();
    }
    bool ok = mode == 1;
    Maps mp;
    if (ok) {
        const cuuint32_t bkv[3] = {64, 64, 2}, bwq[2] = {64, 64}, bwq8[3] = {64, 64, 8}, bwo[4] = {64, 16, 4, 8};
        const cuuint32_t bw1[3] = {64, 64, 4}, bw2[3] = {64, 32, 8};
        const cuuint64_t dkv[3] = {64, (cuuint64_t)HKV_ * SK_, 2}, skv[2] = {256, 128};
        const cuuint64_t dwq[2] = {4096, 512}, swq[1] = {8192};
        const cuuint64_t dwq8[3] = {64, 512, 64}, swq8[2] = {8192, 128};
        const cuuint64_t dwo[4] = {64, 128, 32, 8}, swo[3] = {1024, 131072, 128};
        const cuuint64_t dw1[3] = {64, 512, FF_ / 64}, sw1[2] = {FF_ * 2, 128};
        const cuuint64_t dw2[3] = {64, FF_, 8}, sw2[2] = {1024, 128};
        ok = make_map(enc, &mp.k, kc, 3, dkv, skv, bkv) && make_map(enc, &mp.v, vc, 3, dkv, skv, bkv) &&
             make_map(enc, &mp.wq, wq, 2, dwq, swq, bwq) && make_map(enc, &mp.wq8, wq, 3, dwq8, swq8, bwq8) &&
             make_map(enc, &mp.wo, wo, 4, dwo, swo, bwo) &&
             make_map(enc, &mp.w1, w1, 3, dw1, sw1, bw1) && make_map(enc, &mp.w3, w3, 3, dw1, sw1, bw1) &&
             make_map(enc, &mp.w2, w2, 3, dw2, sw2, bw2);
    }
    if (ok) {
        Ptrs pt = {(const char*)kc, (const char*)vc, (const char*)wq, (const char*)wo, (const char*)w1, (const char*)w3, (const char*)w2};
        cudaLaunchKernelEx(&cfg, fused_kernel, mp, pt, x, out);
        return;
    }
    fb_init<<<1, D_, 0, st>>>(x);
    for (int l = 0; l < 2; l++) {
        fb_qk<<<128, 256, 0, st>>>(wq);
        fb_attn<<<dim3(32, 16), 256, 0, st>>>(kc, vc);
        fb_comb<<<32, 128, 0, st>>>();
        fb_proj<<<16, 1024, 0, st>>>(wo, 4096, 0, nullptr);
        fb_ffn1<<<56, 256, 0, st>>>(w1, w3);
        fb_proj<<<16, 1024, 0, st>>>(w2, FF_, 1, l == 1 ? out : nullptr);
    }
}
```

```cpp
#include <cuda_runtime.h>
#include <cuda_bf16.h>
#include <cuda.h>
#include <stdint.h>

namespace {

typedef unsigned long long u64;
typedef __nv_bfloat16 bf16;

constexpr int D_ = 512, HKV_ = 8, SK_ = 32768, DH_ = 128, WIN_ = 4096, FF_ = 1792;
constexpr int CL = 8;
constexpr int NA = 8, NF = 7;
constexpr int NT = 256;
constexpr float LN_EPS = 1e-5f;
constexpr float QSCALE = 0.08838834764831845f * 1.4426950408889634f;
constexpr int SPIN_LIMIT = 1 << 17;

constexpr int SM_KV = 0;
constexpr int SM_W = 131072;
constexpr int SM_W1 = 0, SM_W3 = 32768, SM_W2 = 65536;
constexpr int SCR = 196608;
constexpr int SM_RS0 = SCR;
constexpr int SM_RS1 = SCR + 4096;
constexpr int SM_RS2 = SCR + 6144;
constexpr int SM_LNST = SCR + 8192;
constexpr int SM_OST = SCR + 8256;
constexpr int SM_XB0 = SCR + 8512;
constexpr int SM_XB1 = SCR + 8640;
constexpr int SM_QB = SCR + 8768;
constexpr int SM_WMAX = SCR + 10048;
constexpr int SM_MREF = SCR + 10176;
constexpr int SM_FLAG = SCR + 10192;
constexpr int SM_ZERO = SCR + 10208;
constexpr int SM_CMAX = SCR + 10240;
constexpr int SM_PART = SCR + 10368;
constexpr int PSTR = 2048 + 64;
constexpr int SM_SCA = SM_RS0;
constexpr int SM_SCB = SM_PART + 8 * PSTR;
constexpr int SM_BAR = SM_SCB + 4096;
constexpr int SM_TLB = SM_BAR + 512;
constexpr int SM_TOTAL = SM_BAR + 512 + 1024;
static_assert(SM_TOTAL <= 232448, "shared memory budget");

constexpr int B_WQ = 0, B_K = 8, B_V = 16, B_WO = 24  , B_WQ2 = 26, B_W1 = 0, B_W3 = 1, B_W2 = 2;
constexpr int B_RSQ = 32, B_QAG = 34, B_RSO = 36, B_RSX = 38, B_RSO2 = 40, B_MX = 41, B_LS = 42, NBAR = 43;

constexpr int PF_KB = 4096;
constexpr int F_DELAY = 8000;
constexpr int F_LAG = 1000;
constexpr int VPRE_N = 2;

__device__ u64 g_af[2][CL][NA][64];
__device__ u64 g_fa[2][CL][NF][64];
__device__ u64 g_go[NA * CL][16];
__device__ unsigned g_epoch = 1;

#define TL(i)

struct __align__(64) Maps { CUtensorMap k, v, wq, wq8, wo, w1, w3, w2; };

__device__ __forceinline__ void mbar_init(uint32_t a, uint32_t cnt) {
    asm volatile("mbarrier.init.shared.b64 [%0], %1;" ::"r"(a), "r"(cnt) : "memory");
}
__device__ __forceinline__ void mbar_expect(uint32_t a, uint32_t bytes) {
    asm volatile("mbarrier.arrive.expect_tx.shared.b64 _, [%0], %1;" ::"r"(a), "r"(bytes) : "memory");
}
__device__ __forceinline__ void mbar_wait(uint32_t a, uint32_t ph) {
    uint32_t ok; int it = 0;
    do {
        asm volatile("{.reg .pred p; mbarrier.try_wait.parity.shared.b64 p, [%1], %2; selp.u32 %0,1,0,p;}"
                     : "=r"(ok) : "r"(a), "r"(ph) : "memory");
    } while (!ok && ++it < SPIN_LIMIT);
}
__device__ __forceinline__ void pin(uint32_t& v) { asm volatile("" : "+r"(v)); }
__device__ __forceinline__ void tma2d(uint32_t dst, const CUtensorMap* m, int c0, int c1, uint32_t bar) {
    asm volatile("cp.async.bulk.tensor.2d.shared::cluster.global.mbarrier::complete_tx::bytes [%0], [%1, {%3, %4}], [%2];"
                 ::"r"(dst), "l"((u64)m), "r"(bar), "r"(c0), "r"(c1) : "memory");
}
__device__ __forceinline__ void tma3d(uint32_t dst, const CUtensorMap* m, int c0, int c1, int c2, uint32_t bar) {
    asm volatile("cp.async.bulk.tensor.3d.shared::cluster.global.mbarrier::complete_tx::bytes [%0], [%1, {%3, %4, %5}], [%2];"
                 ::"r"(dst), "l"((u64)m), "r"(bar), "r"(c0), "r"(c1), "r"(c2) : "memory");
}
__device__ __forceinline__ void tma4d(uint32_t dst, const CUtensorMap* m, int c0, int c1, int c2, int c3, uint32_t bar) {
    asm volatile("cp.async.bulk.tensor.4d.shared::cluster.global.mbarrier::complete_tx::bytes [%0], [%1, {%3, %4, %5, %6}], [%2];"
                 ::"r"(dst), "l"((u64)m), "r"(bar), "r"(c0), "r"(c1), "r"(c2), "r"(c3) : "memory");
}
__device__ __forceinline__ void l2pf(const char* p, uint32_t bytes) {
    asm volatile("cp.async.bulk.prefetch.L2.global [%0], %1;" ::"l"(p), "r"(bytes) : "memory");
}
__device__ __forceinline__ uint32_t mapa(uint32_t a, uint32_t rank) {
    uint32_t r; asm("mapa.shared::cluster.u32 %0, %1, %2;" : "=r"(r) : "r"(a), "r"(rank)); return r;
}
__device__ __forceinline__ void st_async4(uint32_t a, float x, float y, float z, float w, uint32_t bar) {
    asm volatile("st.async.weak.shared::cluster.mbarrier::complete_tx::bytes.v4.f32 [%0], {%1,%2,%3,%4}, [%5];"
                 ::"r"(a), "f"(x), "f"(y), "f"(z), "f"(w), "r"(bar) : "memory");
}
__device__ __forceinline__ void st_async2(uint32_t a, float x, float y, uint32_t bar) {
    asm volatile("st.async.weak.shared::cluster.mbarrier::complete_tx::bytes.v2.f32 [%0], {%1,%2}, [%3];"
                 ::"r"(a), "f"(x), "f"(y), "r"(bar) : "memory");
}
__device__ __forceinline__ void st_async1(uint32_t a, uint32_t x, uint32_t bar) {
    asm volatile("st.async.weak.shared::cluster.mbarrier::complete_tx::bytes.b32 [%0], %1, [%2];"
                 ::"r"(a), "r"(x), "r"(bar) : "memory");
}
__device__ __forceinline__ void ldsm4(uint32_t (&r)[4], uint32_t a) {
    asm volatile("ldmatrix.sync.aligned.m8n8.x4.shared.b16 {%0,%1,%2,%3}, [%4];"
                 : "=r"(r[0]), "=r"(r[1]), "=r"(r[2]), "=r"(r[3]) : "r"(a) : "memory");
}
__device__ __forceinline__ void ldsm4t(uint32_t (&r)[4], uint32_t a) {
    asm volatile("ldmatrix.sync.aligned.m8n8.x4.trans.shared.b16 {%0,%1,%2,%3}, [%4];"
                 : "=r"(r[0]), "=r"(r[1]), "=r"(r[2]), "=r"(r[3]) : "r"(a) : "memory");
}
__device__ __forceinline__ void mma(float (&c)[4], const uint32_t (&a)[4], uint32_t b0, uint32_t b1) {
    asm volatile("mma.sync.aligned.m16n8k16.row.col.f32.bf16.bf16.f32 {%0,%1,%2,%3},{%4,%5,%6,%7},{%8,%9},{%0,%1,%2,%3};"
                 : "+f"(c[0]), "+f"(c[1]), "+f"(c[2]), "+f"(c[3])
                 : "r"(a[0]), "r"(a[1]), "r"(a[2]), "r"(a[3]), "r"(b0), "r"(b1));
}
__device__ __forceinline__ uint4 lds128(uint32_t a) {
    uint4 v; asm volatile("ld.shared.v4.u32 {%0,%1,%2,%3}, [%4];" : "=r"(v.x), "=r"(v.y), "=r"(v.z), "=r"(v.w) : "r"(a) : "memory"); return v;
}
__device__ __forceinline__ float lds32f(uint32_t a) {
    float v; asm volatile("ld.shared.f32 %0, [%1];" : "=f"(v) : "r"(a) : "memory"); return v;
}
__device__ __forceinline__ uint32_t lds32(uint32_t a) {
    uint32_t v; asm volatile("ld.shared.u32 %0, [%1];" : "=r"(v) : "r"(a) : "memory"); return v;
}
__device__ __forceinline__ unsigned short lds16(uint32_t a) {
    unsigned short v; asm volatile("ld.shared.u16 %0, [%1];" : "=h"(v) : "r"(a) : "memory"); return v;
}
__device__ __forceinline__ float2 lds64f(uint32_t a) {
    float2 v; asm volatile("ld.shared.v2.f32 {%0,%1}, [%2];" : "=f"(v.x), "=f"(v.y) : "r"(a) : "memory"); return v;
}
__device__ __forceinline__ void sts16(uint32_t a, unsigned short v) {
    asm volatile("st.shared.u16 [%0], %1;" ::"r"(a), "h"(v) : "memory");
}
__device__ __forceinline__ void sts32(uint32_t a, uint32_t v) {
    asm volatile("st.shared.u32 [%0], %1;" ::"r"(a), "r"(v) : "memory");
}
__device__ __forceinline__ void sts64(uint32_t a, uint32_t x, uint32_t y) {
    asm volatile("st.shared.v2.u32 [%0], {%1,%2};" ::"r"(a), "r"(x), "r"(y) : "memory");
}
__device__ __forceinline__ float ex2(float x) { float y; asm("ex2.approx.ftz.f32 %0, %1;" : "=f"(y) : "f"(x)); return y; }
__device__ __forceinline__ uint32_t pack_bf16(float lo, float hi) {
    uint32_t r; asm("cvt.rn.bf16x2.f32 %0, %1, %2;" : "=r"(r) : "f"(hi), "f"(lo)); return r;
}
__device__ __forceinline__ int f2ord(float x) { int i = __float_as_int(x); return i ^ ((i >> 31) & 0x7fffffff); }
__device__ __forceinline__ float ord2f(int i) { return __int_as_float(i ^ ((i >> 31) & 0x7fffffff)); }
__device__ __forceinline__ void st_pkt(u64* p, float v, unsigned tag) {
    u64 x = ((u64)tag << 32) | __float_as_uint(v);
    asm volatile("st.relaxed.gpu.global.b64 [%0], %1;" ::"l"(p), "l"(x) : "memory");
}
__device__ __forceinline__ u64 ld_pkt(const u64* p) {
    u64 x; asm volatile("ld.relaxed.gpu.global.b64 %0, [%1];" : "=l"(x) : "l"(p) : "memory"); return x;
}
template <int N>
__device__ __forceinline__ float poll_sum(const u64* base, unsigned tag) {
    u64 v[N]; bool ok; int it = 0;
    do {
#pragma unroll
        for (int j = 0; j < N; j++) v[j] = ld_pkt(base + j * 64);
        ok = true;
#pragma unroll
        for (int j = 0; j < N; j++) ok = ok && ((unsigned)(v[j] >> 32) == tag);
    } while (!ok && ++it < SPIN_LIMIT);
    float s[8];
#pragma unroll
    for (int j = 0; j < 8; j++) s[j] = j < N ? __uint_as_float((unsigned)v[j]) : 0.f;
    return ((s[0] + s[1]) + (s[2] + s[3])) + ((s[4] + s[5]) + (s[6] + s[7]));
}

__device__ __forceinline__ int pos2col(int i) { return 16 * (i & 3) + 8 * ((i >> 2) & 1) + (i >> 3); }
__device__ __forceinline__ int kpos64(int k) { return ((k & 7) >> 1) * 16 + (k >> 4) * 4 + ((k >> 3) & 1) * 2 + (k & 1); }
__device__ __forceinline__ int kpos32(int k) { return ((k & 7) >> 1) * 8 + (k >> 4) * 4 + ((k >> 3) & 1) * 2 + (k & 1); }

template <int KT>
__device__ __forceinline__ void load_wfrag(uint32_t (&w)[4][KT][4], uint32_t box, int lane) {
    const int mi = lane >> 3, rr = lane & 7;
    const uint32_t rowa = box + (8 * (mi >> 1) + rr) * 128;
#pragma unroll
    for (int mt = 0; mt < 4; mt++) {
        const uint32_t a = rowa + (((2 * mt + (mi & 1)) ^ rr) << 4);
#pragma unroll
        for (int kt = 0; kt < KT; kt++) ldsm4t(w[mt][kt], a + kt * 2048);
    }
}

template <int KT>
__device__ __forceinline__ void gemv(float (&acc)[4][4], const uint32_t (&w)[4][KT][4], const uint32_t (&b)[2 * KT]) {
#pragma unroll
    for (int mt = 0; mt < 4; mt++) { acc[mt][0] = acc[mt][1] = acc[mt][2] = acc[mt][3] = 0.f; }
#pragma unroll
    for (int kt = 0; kt < KT; kt++)
#pragma unroll
        for (int mt = 0; mt < 4; mt++) mma(acc[mt], w[mt][kt], b[2 * kt], b[2 * kt + 1]);
}
template <bool CS>
__device__ __forceinline__ void gemv_send(const float (&acc)[4][4], int lane, uint32_t dst, uint32_t dbar) {
    const int t = lane & 3;
    float v[4];
#pragma unroll
    for (int mt = 0; mt < 4; mt++) {
        if (CS) v[mt] = (t == 0) ? acc[mt][0] : (t == 1) ? acc[mt][2] : (t == 2) ? acc[mt][1] : acc[mt][3];
        else v[mt] = (t == 0) ? acc[mt][0] : acc[mt][2];
    }
    if (CS || t < 2) st_async4(dst, v[0], v[1], v[2], v[3], dbar);
}

__device__ __forceinline__ float sum8(uint32_t a, int stride) {
    float v[8];
#pragma unroll
    for (int j = 0; j < 8; j++) v[j] = lds32f(a + j * stride);
    return ((v[0] + v[1]) + (v[2] + v[3])) + ((v[4] + v[5]) + (v[6] + v[7]));
}

__device__ __forceinline__ void gemv_ln(float (&acc)[4][4], const uint32_t (&w)[4][4][4], const uint32_t (&bx)[8],
                                        const uint32_t (&b)[8], int warp, int lane, uint32_t sdst, uint32_t sbar) {
    if (warp < 6) { gemv<4>(acc, w, b); return; }
    float st[4] = {0.f, 0.f, 0.f, 0.f};
#pragma unroll
    for (int mt = 0; mt < 4; mt++) { acc[mt][0] = acc[mt][1] = acc[mt][2] = acc[mt][3] = 0.f; }
#pragma unroll
    for (int kt = 0; kt < 4; kt++) {
        const uint32_t lo = warp == 6 ? 0x3f803f80u : bx[2 * kt], hi = warp == 6 ? 0x3f803f80u : bx[2 * kt + 1];
        const uint32_t xa[4] = {lo, lo, hi, hi};
        mma(st, xa, b[2 * kt], b[2 * kt + 1]);
#pragma unroll
        for (int mt = 0; mt < 4; mt++) mma(acc[mt], w[mt][kt], b[2 * kt], b[2 * kt + 1]);
    }
    if ((lane & 3) == 0) st_async1(sdst, __float_as_uint(st[0]), sbar);
}
__device__ __forceinline__ void recv_lnstats(uint32_t sb, float& mean, float& rstd) {
    float a1[4], a2[4];
#pragma unroll
    for (int j = 0; j < 4; j++) {
        uint4 v = lds128(sb + SM_LNST + j * 16);
        a1[j] = __uint_as_float(v.x) + __uint_as_float(v.z);
        a2[j] = __uint_as_float(v.y) + __uint_as_float(v.w);
    }
    const float s1 = (a1[0] + a1[1]) + (a1[2] + a1[3]), s2 = (a2[0] + a2[1]) + (a2[2] + a2[3]);
    mean = s1 * (1.f / D_);
    const float var = fmaxf(s2 * (1.f / D_) - mean * mean, 0.f);
    asm("rsqrt.approx.ftz.f32 %0, %1;" : "=f"(rstd) : "f"(var + LN_EPS));
}

struct Ctx {
    uint32_t sb;
    int tid, lane, warp, rank, cid;
    unsigned tag;
};

template <int MODE>
__device__ __forceinline__ void attn_pv(const Ctx& c, const float (&sa)[4], const float (&sbv)[4], float rA, float rB,
                                        uint32_t (&vf)[4][8][4], const uint32_t (&va)[4], uint32_t lsbar,
                                        uint32_t rdst, uint32_t sdst, uint32_t rbar, uint32_t (&wf)[4][4][4]) {
    const uint32_t sb = c.sb;
    const int lane = c.lane, warp = c.warp, lg = lane >> 2, lt = lane & 3, hp = lt & 1;
    const int NEG = (int)0x80000000;
    constexpr bool EXACT = MODE == 2;
    float fA = rA, fB = rB;
    if (EXACT) {
        const int mA = f2ord(fmaxf(fmaxf(sa[0], sa[1]), fmaxf(sa[2], sa[3])));
        const int mB = f2ord(fmaxf(fmaxf(sbv[0], sbv[1]), fmaxf(sbv[2], sbv[3])));
        const int r0 = __reduce_max_sync(~0u, hp == 0 ? mA : NEG);
        const int r1 = __reduce_max_sync(~0u, hp == 0 ? mB : NEG);
        const int r2 = __reduce_max_sync(~0u, hp == 1 ? mA : NEG);
        const int r3 = __reduce_max_sync(~0u, hp == 1 ? mB : NEG);
        const int wA = hp == 0 ? r0 : r2, wB = hp == 0 ? r1 : r3;
        fA = ord2f(wA) * QSCALE; fB = ord2f(wB) * QSCALE;
        if (lane < 2) sts64(sb + SM_WMAX + lane * 64 + warp * 8, wA, wB);
        __syncwarp();
        if (lane == 0) asm volatile("mbarrier.arrive.shared.b64 _, [%0];" ::"r"(lsbar) : "memory");
    }
    uint32_t b0[4], b1[4];
#pragma unroll
    for (int T = 0; T < 4; T++) {
        const uint32_t pk = pack_bf16(ex2(fmaf(sa[T], QSCALE, -fA)), ex2(fmaf(sbv[T], QSCALE, -fB)));
        asm volatile("movmatrix.sync.aligned.m8n8.trans.b16 %0, %1;" : "=r"(b0[T]) : "r"(pk));
        b1[T] = __shfl_down_sync(~0u, b0[T], 16);
    }
    if (MODE == 1) {
        load_wfrag<4>(wf, sb + SM_W + warp * 8192, lane);
        uint32_t z = 0;
#pragma unroll
        for (int i = 0; i < 16; i++) z |= wf[i >> 2][i & 3][0];
        b0[2] |= z & lds32(sb + SM_ZERO);
    }
    float oc[8][4], lc[4];
#pragma unroll
    for (int m = 0; m < 8; m++) { oc[m][0] = oc[m][1] = oc[m][2] = oc[m][3] = 0.f; }
    lc[0] = lc[1] = lc[2] = lc[3] = 0.f;
    const uint32_t ones[4] = {0x3f803f80u, 0x3f803f80u, 0x3f803f80u, 0x3f803f80u};
    if (MODE == 0) { mbar_wait(sb + SM_BAR + 8 * (B_V + warp), 0); TL(27); }
#pragma unroll
    for (int T = 0; T < 4; T++) {
        if (MODE != 1) {
#pragma unroll
            for (int m = 0; m < 8; m++) ldsm4t(vf[T][m], va[m & 3] + (m >> 2) * 8192 + T * 2048);
        }
#pragma unroll
        for (int m = 0; m < 8; m++) mma(oc[m], vf[T][m], b0[T], b1[T]);
        mma(lc, ones, b0[T], b1[T]);
    }
    if (MODE == 1) TL(34);
    float gA = 1.f, gB = 1.f;
    if (EXACT) {
        mbar_wait(lsbar, 0);
        int MA = NEG, MB = NEG;
#pragma unroll
        for (int j = 0; j < 4; j++) {
            uint4 v = lds128(sb + SM_WMAX + hp * 64 + j * 16);
            MA = max(MA, max((int)v.x, (int)v.z)); MB = max(MB, max((int)v.y, (int)v.w));
        }
        const float fMA = ord2f(MA) * QSCALE, fMB = ord2f(MB) * QSCALE;
        gA = ex2(fA - fMA); gB = ex2(fB - fMB);
        fA = fMA; fB = fMB;
    }
    if (lt < 2) {
        const uint32_t pw = sb + SM_PART + warp * PSTR + (lg * 2 + lt) * 16;
#pragma unroll
        for (int m = 0; m < 8; m++) {
            if (EXACT) { oc[m][0] *= gA; oc[m][1] *= gB; oc[m][2] *= gA; oc[m][3] *= gB; }
            asm volatile("st.shared.v4.f32 [%0], {%1,%2,%3,%4};" ::"r"(pw + m * 256), "f"(oc[m][0]), "f"(oc[m][1]),
                         "f"(oc[m][2]), "f"(oc[m][3]) : "memory");
        }
        if (lg == 0) sts64(sb + SM_PART + warp * PSTR + 2048 + lt * 8, __float_as_uint(lc[0] * gA), __float_as_uint(lc[1] * gB));
    }
    if (MODE == 1) TL(36);
    __syncthreads();
    float2 v[8], u[8];
#pragma unroll
    for (int w = 0; w < 8; w++) v[w] = lds64f(sb + SM_PART + c.tid * 8 + w * PSTR);
    if (lane < 2) {
#pragma unroll
        for (int w = 0; w < 8; w++) u[w] = lds64f(sb + SM_PART + w * PSTR + 2048 + lane * 8);
    }
    st_async2(rdst, ((v[0].x + v[1].x) + (v[2].x + v[3].x)) + ((v[4].x + v[5].x) + (v[6].x + v[7].x)),
              ((v[0].y + v[1].y) + (v[2].y + v[3].y)) + ((v[4].y + v[5].y) + (v[6].y + v[7].y)), rbar);
    if (lane < 2)
        st_async4(sdst, fA, ((u[0].x + u[1].x) + (u[2].x + u[3].x)) + ((u[4].x + u[5].x) + (u[6].x + u[7].x)),
                  fB, ((u[0].y + u[1].y) + (u[2].y + u[3].y)) + ((u[4].y + u[5].y) + (u[6].y + u[7].y)), rbar);
}

__device__ __forceinline__ float combine_exact(uint32_t sta, uint32_t ra) {
    float2 st[8]; float pv[8];
#pragma unroll
    for (int s = 0; s < 8; s++) st[s] = lds64f(sta + s * 32);
#pragma unroll
    for (int s = 0; s < 8; s++) pv[s] = lds32f(ra + s * 256);
    const float M = fmaxf(fmaxf(fmaxf(st[0].x, st[1].x), fmaxf(st[2].x, st[3].x)), fmaxf(fmaxf(st[4].x, st[5].x), fmaxf(st[6].x, st[7].x)));
    float f[8];
#pragma unroll
    for (int s = 0; s < 8; s++) f[s] = ex2(st[s].x - M);
    const float num = ((f[0] * pv[0] + f[1] * pv[1]) + (f[2] * pv[2] + f[3] * pv[3])) + ((f[4] * pv[4] + f[5] * pv[5]) + (f[6] * pv[6] + f[7] * pv[7]));
    const float den = ((f[0] * st[0].y + f[1] * st[1].y) + (f[2] * st[2].y + f[3] * st[3].y)) + ((f[4] * st[4].y + f[5] * st[5].y) + (f[6] * st[6].y + f[7] * st[7].y));
    return __fdividef(num, den);
}

__device__ __noinline__ void attn_redo(uint32_t sb) {
    Ctx c;
    c.sb = sb; c.tid = threadIdx.x; c.lane = c.tid & 31; c.warp = c.tid >> 5;
    c.rank = blockIdx.x % CL; c.cid = blockIdx.x / CL; c.tag = 0;
    const int lane = c.lane, warp = c.warp, tid = c.tid, rank = c.rank;
    const uint32_t bar = sb + SM_BAR;
    const uint4 ua = lds128(sb + SM_SCA + tid * 16), ub = lds128(sb + SM_SCB + tid * 16);
    const float sa[4] = {__uint_as_float(ua.x), __uint_as_float(ua.y), __uint_as_float(ua.z), __uint_as_float(ua.w)};
    const float sbv[4] = {__uint_as_float(ub.x), __uint_as_float(ub.y), __uint_as_float(ub.z), __uint_as_float(ub.w)};
    uint32_t vf[4][8][4], va[4], wf[4][4][4];
    const int mi = lane >> 3, rr = lane & 7;
#pragma unroll
    for (int m = 0; m < 4; m++)
        va[m] = sb + SM_KV + warp * 16384 + (8 * (mi >> 1) + rr) * 128 + (((2 * m + (mi & 1)) ^ rr) << 4);
    asm volatile("barrier.cluster.arrive.aligned;\n\tbarrier.cluster.wait.aligned;" ::: "memory");
    attn_pv<2>(c, sa, sbv, 0.f, 0.f, vf, va, bar + 8 * B_LS,
                            mapa(sb + SM_RS1 + rank * 256 + lane * 8, warp),
                            mapa(sb + SM_OST + rank * 32 + (lane & 1) * 16, warp), mapa(bar + 8 * B_RSO2, warp), wf);
    if (warp < 2) {
        const int j = tid & 3, head = 2 * ((tid >> 2) & 1) + (j & 1), dd = ((tid >> 3) & 7) + 8 * (j >> 1);
        mbar_wait(bar + 8 * B_RSO2, 0);
        const float o = combine_exact(sb + SM_OST + head * 8, sb + SM_RS1 + tid * 4);
        sts16(sb + SM_XB1 + 2 * kpos64(head * 16 + dd), __bfloat16_as_ushort(__float2bfloat16(o)));
    }
    __syncthreads();
}

template <int L>
__device__ __forceinline__ void attn_layer(const Ctx& c, const Maps& mp, unsigned short x0raw,
                                           uint32_t (&kf)[4][8][4], float& cs) {
    const uint32_t sb = c.sb;
    const int lane = c.lane, warp = c.warp, tid = c.tid, rank = c.rank, g = c.cid;
    const int lg = lane >> 2, lt = lane & 3;
    const uint32_t bar = sb + SM_BAR;
    const uint32_t wbox = sb + SM_W + warp * 8192;

    if (L == 0) {
        const uint32_t kb = sb + SM_KV + warp * 16384;
        mbar_wait(bar + 8 * (B_K + warp), 0);
        TL(25);
        const int mi = lane >> 3, rr = lane & 7;
#pragma unroll
        for (int T = 0; T < 4; T++) {
            const uint32_t rowa = kb + (16 * T + 8 * (mi & 1) + rr) * 128;
#pragma unroll
            for (int s = 0; s < 8; s++)
                ldsm4(kf[T][s], rowa + (s >> 2) * 8192 + (((2 * (s & 3) + (mi >> 1)) ^ rr) << 4));
        }
        uint32_t dep = 0;
#pragma unroll
        for (int T = 0; T < 4; T++)
#pragma unroll
            for (int s = 0; s < 8; s++) dep |= kf[T][s][0];
        dep = __reduce_or_sync(~0u, dep) & lds32(sb + SM_ZERO);
        if (lane == 0) {
            const int row = g * SK_ + (SK_ - WIN_) + rank * 512 + warp * 64 + (int)dep;
            mbar_expect(bar + 8 * (B_V + warp), 16384);
            tma3d(kb, &mp.v, 0, row, 0, bar + 8 * (B_V + warp));
        }
    }
    {
        uint32_t wf[4][4][4];
        mbar_wait(bar + 8 * (L == 0 ? B_WQ + warp : B_WQ2), 0);
        load_wfrag<4>(wf, wbox, lane);
        if (L == 1) {
            __syncthreads();
            if (tid == 64) {
                mbar_expect(bar + 8 * (B_WO + 1), 65536);
                tma4d(sb + SM_W, &mp.wo, 0, 16 * rank, 4 * g, 0, bar + 8 * (B_WO + 1));
            }
        }
        uint32_t xa = sb + SM_XB0 + 2 * kpos64(pos2col(tid & 63));
        uint32_t dst = mapa(sb + SM_RS0 + rank * 512 + (L == 0 ? (lt >> 1) * 256 : 0) + (lg * 2 + (lt & 1)) * 16, warp), dbar = mapa(bar + 8 * (B_RSQ + L), warp);
        uint32_t ba = sb + SM_XB0 + lt * 32;
        uint32_t sdst = mapa(sb + SM_LNST + rank * 8 + (warp & 1) * 4, lg), sbar = mapa(bar + 8 * (B_RSQ + L), lg);
        pin(xa); pin(dst); pin(dbar); pin(ba); pin(sdst); pin(sbar);
        TL(L * 12 + 1);
        if (warp < 2) {
            unsigned short xb = x0raw;
            if (L == 1) xb = __bfloat16_as_ushort(__float2bfloat16(poll_sum<NF>(&g_fa[0][rank][0][tid], c.tag)));
            sts16(xa, xb);
        }
        TL(L * 12 + 2);
        __syncthreads();
        uint32_t bx[8], b[8];
        {
            uint4 v0 = lds128(ba), v1 = lds128(ba + 16);
            bx[0] = v0.x; bx[1] = v0.y; bx[2] = v0.z; bx[3] = v0.w; bx[4] = v1.x; bx[5] = v1.y; bx[6] = v1.z; bx[7] = v1.w;
#pragma unroll
            for (int j = 0; j < 8; j++) b[j] = (L == 0 && (lg == 5 || lg == 7)) ? 0x3f803f80u : bx[j];
        }
        float acc[4][4];
        gemv_ln(acc, wf, bx, b, warp, lane, sdst, sbar);
        gemv_send<L == 0>(acc, lane, dst, dbar);
        if (L == 0 && tid == 64) {
            mbar_expect(bar + 8 * (B_WO + L), 65536);
            tma4d(sb + SM_W, &mp.wo, 0, 16 * rank, 4 * g, 0, bar + 8 * (B_WO + L));
            st_pkt(&g_go[g * CL + rank][0], 0.f, c.tag);
        }
    }
    TL(L * 12 + 3);
    constexpr int VPRE = (L == 1) ? VPRE_N : 0;
    uint32_t vf[4][8][4];
    uint32_t va[4];
    {
        const int mi = lane >> 3, rr = lane & 7;
#pragma unroll
        for (int m = 0; m < 4; m++)
            va[m] = sb + SM_KV + warp * 16384 + (8 * (mi >> 1) + rr) * 128 + (((2 * m + (mi & 1)) ^ rr) << 4);
    }
    if (warp < 2) {
        const bool odd = (tid >> 3) & 1;
        const int tql = (lane >> 1) & 1, sp = lane & 1;
        uint32_t da = mapa(sb + SM_QB + (rank >> 1) * 320 + (2 * warp + tql) * 80 + (2 * (rank & 1) + sp) * 16, lane >> 2);
        uint32_t db = mapa(bar + 8 * (B_QAG + L), lane >> 2);
        uint32_t ra = sb + SM_RS0 + tid * 4;
        pin(da); pin(db); pin(ra);
        mbar_wait(bar + 8 * (B_RSQ + L), 0);
        const float v = sum8(ra, 512);
        if (L == 0) cs = sum8(ra + 256, 512);
        float mean, rstd;
        recv_lnstats(sb, mean, rstd);
        const float q = (v - mean * cs) * rstd;
        const float qo = __shfl_xor_sync(~0u, q, 8);
        const uint32_t word = odd ? pack_bf16(qo, q) : pack_bf16(q, qo);
        const int src = 2 * sp + 16 * tql;
        const uint32_t w0 = __shfl_sync(~0u, word, src), w1 = __shfl_sync(~0u, word, src + 4);
        const uint32_t w2 = __shfl_sync(~0u, word, src + 1), w3 = __shfl_sync(~0u, word, src + 5);
        st_async4(da, __uint_as_float(w0), __uint_as_float(w1), __uint_as_float(w2), __uint_as_float(w3), db);
    }
    __syncwarp();
#pragma unroll
    for (int T = 0; T < VPRE; T++)
#pragma unroll
        for (int m = 0; m < 8; m++) ldsm4t(vf[T][m], va[m & 3] + (m >> 2) * 8192 + T * 2048);
    TL(L * 12 + 4);
    float sa[4], sbv[4];
    uint32_t wf[4][4][4];
    {
        const int hp = lt & 1;
        uint32_t qa = sb + SM_QB + (lg & 3) * 320 + lt * 80;
        uint32_t rdst = mapa(sb + SM_RS1 + rank * 256 + lane * 8, warp), rbar = mapa(bar + 8 * (B_RSO + L), warp);
        uint32_t sdst = mapa(sb + SM_OST + rank * 32 + hp * 16, warp);
        float2 ref = make_float2(0.f, 0.f);
        if (L == 1) ref = lds64f(sb + SM_MREF + hp * 8);
        pin(qa); pin(rdst); pin(rbar); pin(sdst);
        if (L == 1) mbar_wait(bar + 8 * (B_WO + 1), 0);
        mbar_wait(bar + 8 * (B_QAG + L), 0);
        TL(L * 12 + 5);
        uint32_t qb[16];
#pragma unroll
        for (int i = 0; i < 4; i++) {
            uint4 v = lds128(qa + i * 16);
            qb[4 * i] = v.x; qb[4 * i + 1] = v.y; qb[4 * i + 2] = v.z; qb[4 * i + 3] = v.w;
        }
        float sc[4][4];
#pragma unroll
        for (int T = 0; T < 4; T++) { sc[T][0] = sc[T][1] = sc[T][2] = sc[T][3] = 0.f; }
#pragma unroll
        for (int s = 0; s < 8; s++)
#pragma unroll
            for (int T = 0; T < 4; T++) mma(sc[T], kf[T][s], qb[2 * s], qb[2 * s + 1]);
        if (L == 1) {
#pragma unroll
            for (int T = VPRE; T < 4; T++)
#pragma unroll
                for (int m = 0; m < 8; m++) ldsm4t(vf[T][m], va[m & 3] + (m >> 2) * 8192 + T * 2048);
        }
        if (L == 1) TL(32);
#pragma unroll
        for (int T = 0; T < 4; T++) { sa[T] = (lt < 2) ? sc[T][0] : sc[T][2]; sbv[T] = (lt < 2) ? sc[T][1] : sc[T][3]; }
        if (L == 1) {
            asm volatile("st.shared.v4.f32 [%0], {%1,%2,%3,%4};" ::"r"(sb + SM_SCA + tid * 16), "f"(sa[0]), "f"(sa[1]), "f"(sa[2]), "f"(sa[3]) : "memory");
            asm volatile("st.shared.v4.f32 [%0], {%1,%2,%3,%4};" ::"r"(sb + SM_SCB + tid * 16), "f"(sbv[0]), "f"(sbv[1]), "f"(sbv[2]), "f"(sbv[3]) : "memory");
        }
        if (L == 0) {
            const int NEG = (int)0x80000000;
            const int mA = f2ord(fmaxf(fmaxf(sa[0], sa[1]), fmaxf(sa[2], sa[3])));
            const int mB = f2ord(fmaxf(fmaxf(sbv[0], sbv[1]), fmaxf(sbv[2], sbv[3])));
            const int r0 = __reduce_max_sync(~0u, hp == 0 ? mA : NEG);
            const int r1 = __reduce_max_sync(~0u, hp == 0 ? mB : NEG);
            const int r2 = __reduce_max_sync(~0u, hp == 1 ? mA : NEG);
            const int r3 = __reduce_max_sync(~0u, hp == 1 ? mB : NEG);
            if (lane < 2) sts64(sb + SM_WMAX + lane * 64 + warp * 8, lane == 0 ? r0 : r2, lane == 0 ? r1 : r3);
            __syncthreads();
            int MA = NEG, MB = NEG;
#pragma unroll
            for (int j = 0; j < 4; j++) {
                uint4 v = lds128(sb + SM_WMAX + hp * 64 + j * 16);
                MA = max(MA, max((int)v.x, (int)v.z)); MB = max(MB, max((int)v.y, (int)v.w));
            }
            if (lane < 2)
                st_async2(mapa(sb + SM_CMAX + lane * 64 + rank * 8, warp), __int_as_float(MA), __int_as_float(MB), mapa(bar + 8 * B_MX, warp));
            mbar_wait(bar + 8 * B_MX, 0);
#pragma unroll
            for (int j = 0; j < 4; j++) {
                uint4 v = lds128(sb + SM_CMAX + hp * 64 + j * 16);
                MA = max(MA, max((int)v.x, (int)v.z)); MB = max(MB, max((int)v.y, (int)v.w));
            }
            ref = make_float2(ord2f(MA) * QSCALE, ord2f(MB) * QSCALE);
            if (tid < 2) sts64(sb + SM_MREF + tid * 8, __float_as_uint(ref.x + 8.f), __float_as_uint(ref.y + 8.f));
        }
        attn_pv<L>(c, sa, sbv, ref.x, ref.y, vf, va, 0, rdst, sdst, rbar, wf);
    }
    TL(L * 12 + 7);
    {
        uint32_t dst = mapa(sb + SM_RS2 + rank * 256 + (lg * 2 + (lt & 1)) * 16, warp), dbar = mapa(bar + 8 * (B_RSX + L), warp);
        uint32_t ba = sb + SM_XB1 + lt * 32;
        pin(dst); pin(dbar); pin(ba);
        const int j = tid & 3, head = 2 * ((tid >> 2) & 1) + (j & 1), dd = ((tid >> 3) & 7) + 8 * (j >> 1);
        uint32_t xa = sb + SM_XB1 + 2 * kpos64(head * 16 + dd);
        if (warp >= 2) {
            if (L == 0) {
                mbar_wait(bar + 8 * B_WO, 0);
                TL(29);
                load_wfrag<4>(wf, wbox, lane);
            }
        } else {
            uint32_t sta = sb + SM_OST + head * 8, ra = sb + SM_RS1 + tid * 4;
            pin(sta); pin(ra); pin(xa);
            mbar_wait(bar + 8 * (B_RSO + L), 0);
            TL(L * 12 + 8);
            const float den = sum8(sta + 4, 32), num = sum8(ra, 256);
            sts16(xa, __bfloat16_as_ushort(__float2bfloat16(__fdividef(num, den))));
            if (L == 0) {
                mbar_wait(bar + 8 * B_WO, 0);
                load_wfrag<4>(wf, wbox, lane);
            } else {
                const bool bad = !(den >= 9.1e-13f && den <= 4096.f);
                const unsigned anyb = __ballot_sync(~0u, bad);
                if (lane == 0) sts32(sb + SM_FLAG + warp * 4, anyb);
            }
        }
        __syncthreads();
        float acc[4][4];
        {
            const uint4 v0 = lds128(ba), v1 = lds128(ba + 16);
            const uint32_t b[8] = {v0.x, v0.y, v0.z, v0.w, v1.x, v1.y, v1.z, v1.w};
            gemv<4>(acc, wf, b);
        }
        if (L == 1) {
            const float2 fl = lds64f(sb + SM_FLAG);
            if (__builtin_expect((__float_as_uint(fl.x) | __float_as_uint(fl.y)) != 0, 0)) {
                attn_redo(sb);
                load_wfrag<4>(wf, wbox, lane);
                const uint4 v0 = lds128(ba), v1 = lds128(ba + 16);
                const uint32_t b[8] = {v0.x, v0.y, v0.z, v0.w, v1.x, v1.y, v1.z, v1.w};
                gemv<4>(acc, wf, b);
            }
        }
        gemv_send<false>(acc, lane, dst, dbar);
        if (L == 0 && tid == 64) {
            mbar_expect(bar + 8 * B_WQ2, 65536);
            tma3d(sb + SM_W, &mp.wq8, 0, 64 * rank, 8 * g, bar + 8 * B_WQ2);
        }
    }
    TL(L * 12 + 9);
    if (warp < 2) {
        float xres = 0.f;
        if (g == 0) xres = __uint_as_float((uint32_t)lds16(sb + SM_XB0 + 2 * kpos64(pos2col(tid))) << 16);
        u64* gp = &g_af[L][rank][g][tid];
        uint32_t ra = sb + SM_RS2 + tid * 4;
        asm volatile("" : "+l"(gp), "+f"(xres)); pin(ra);
        mbar_wait(bar + 8 * (B_RSX + L), 0);
        st_pkt(gp, sum8(ra, 256) + xres, c.tag);
    }
    TL(L * 12 + 10);
}

template <int L>
__device__ __forceinline__ void ffn_layer(const Ctx& c, uint32_t (&w13)[4][4][4], uint32_t (&w2)[4][2][4], float& cs) {
    const uint32_t sb = c.sb;
    const int lane = c.lane, warp = c.warp, tid = c.tid, rank = c.rank, fc = c.cid - NA;
    const int lg = lane >> 2, lt = lane & 3;
    const uint32_t bar = sb + SM_BAR;
    if (L == 0) {
        const int mi = lane >> 3, rr = lane & 7;
        mbar_wait(bar + 8 * B_W1, 0);
        mbar_wait(bar + 8 * B_W3, 0);
#pragma unroll
        for (int mt = 0; mt < 4; mt++) {
            const uint32_t box = sb + (mt < 2 ? SM_W1 : SM_W3) + (warp >> 1) * 8192;
            const uint32_t a = box + (8 * (mi >> 1) + rr) * 128 + (((4 * (warp & 1) + 2 * (mt & 1) + (mi & 1)) ^ rr) << 4);
#pragma unroll
            for (int kt = 0; kt < 4; kt++) ldsm4t(w13[mt][kt], a + kt * 2048);
        }
    }
    {
        uint32_t xa = sb + SM_XB0 + 2 * kpos64(pos2col(tid & 63));
        uint32_t dst = mapa(sb + SM_RS0 + rank * 512 + (L == 0 ? (lt >> 1) * 256 : 0) + (lg * 2 + (lt & 1)) * 16, warp), dbar = mapa(bar + 8 * (B_RSQ + L), warp);
        uint32_t ba = sb + SM_XB0 + lt * 32;
        uint32_t sdst = mapa(sb + SM_LNST + rank * 8 + (warp & 1) * 4, lg), sbar = mapa(bar + 8 * (B_RSQ + L), lg);
        pin(xa); pin(dst); pin(dbar); pin(ba); pin(sdst); pin(sbar);
        TL(L * 12 + 1);
        if (warp < 2) sts16(xa, __bfloat16_as_ushort(__float2bfloat16(poll_sum<NA>(&g_af[L][rank][0][tid], c.tag))));
        TL(L * 12 + 2);
        __syncthreads();
        uint32_t bx[8], b[8];
        {
            uint4 v0 = lds128(ba), v1 = lds128(ba + 16);
            bx[0] = v0.x; bx[1] = v0.y; bx[2] = v0.z; bx[3] = v0.w; bx[4] = v1.x; bx[5] = v1.y; bx[6] = v1.z; bx[7] = v1.w;
#pragma unroll
            for (int j = 0; j < 8; j++) b[j] = (L == 0 && (lg == 5 || lg == 7)) ? 0x3f803f80u : bx[j];
        }
        float acc[4][4];
        gemv_ln(acc, w13, bx, b, warp, lane, sdst, sbar);
        gemv_send<L == 0>(acc, lane, dst, dbar);
    }
    TL(L * 12 + 3);
    {
        uint32_t dst = mapa(sb + SM_RS2 + rank * 256 + (lg * 2 + (lt & 1)) * 16, warp), dbar = mapa(bar + 8 * (B_RSX + L), warp);
        uint32_t ba = sb + SM_XB1 + lt * 16;
        pin(dst); pin(dbar); pin(ba);
        if (L == 0 && warp >= 2) {
            mbar_wait(bar + 8 * B_W2, 0);
            load_wfrag<2>(w2, sb + SM_W2 + warp * 4096, lane);
        }
        TL(L * 12 + 4);
        if (warp < 2) {
            const int hidx = 16 * (tid & 1) + 8 * ((tid >> 2) & 1) + (tid >> 3);
            uint32_t ra = sb + SM_RS0 + tid * 4, xa = sb + SM_XB1 + 2 * kpos32(hidx);
            pin(ra); pin(xa);
            mbar_wait(bar + 8 * (B_RSQ + L), 0);
            TL(L * 12 + 5);
            const float v = sum8(ra, 512);
            if (L == 0) cs = sum8(ra + 256, 512);
            float mean, rstd;
            recv_lnstats(sb, mean, rstd);
            const float y = (v - mean * cs) * rstd;
            const float yo = __shfl_xor_sync(~0u, y, 2);
            const float h = __fdividef(y, 1.f + ex2(-1.4426950408889634f * y)) * yo;
            if ((tid & 2) == 0) sts16(xa, __bfloat16_as_ushort(__float2bfloat16(h)));
            if (L == 0) {
                mbar_wait(bar + 8 * B_W2, 0);
                load_wfrag<2>(w2, sb + SM_W2 + warp * 4096, lane);
            }
        }
        __syncthreads();
        uint32_t b[4];
        uint4 v0 = lds128(ba);
        b[0] = v0.x; b[1] = v0.y; b[2] = v0.z; b[3] = v0.w;
        float acc[4][4];
        gemv<2>(acc, w2, b);
        gemv_send<false>(acc, lane, dst, dbar);
    }
    TL(L * 12 + 6);
    if (warp < 2) {
        float xres = 0.f;
        if (fc == 0) xres = __uint_as_float((uint32_t)lds16(sb + SM_XB0 + 2 * kpos64(pos2col(tid))) << 16);
        u64* gp = &g_fa[L][rank][fc][tid];
        uint32_t ra = sb + SM_RS2 + tid * 4;
        asm volatile("" : "+l"(gp), "+f"(xres)); pin(ra);
        mbar_wait(bar + 8 * (B_RSX + L), 0);
        st_pkt(gp, sum8(ra, 256) + xres, c.tag);
    }
    TL(L * 12 + 7);
}

__global__ void __launch_bounds__(NT, 1)
fused_kernel(const char* __restrict__ kptr, const bf16* __restrict__ xin, bf16* __restrict__ out, const __grid_constant__ Maps mp) {
    extern __shared__ unsigned char smem_raw[];
    Ctx c;
    c.sb = ((uint32_t)__cvta_generic_to_shared(smem_raw) + 1023u) & ~1023u;
    c.tid = threadIdx.x; c.lane = c.tid & 31; c.warp = c.tid >> 5;
    c.rank = blockIdx.x % CL; c.cid = blockIdx.x / CL;
    const uint32_t sb = c.sb, bar = sb + SM_BAR;
    const bool isA = c.cid < NA;
    const long long t0 = clock64();
    if (isA && c.lane == 0) {
        const int g = c.cid, w = c.warp;
        const int row = g * SK_ + (SK_ - WIN_) + c.rank * 512 + w * 64;
        l2pf(kptr + (size_t)row * 256, PF_KB);
        TL(40);
        mbar_init(bar + 8 * (B_WQ + w), 1);
        mbar_init(bar + 8 * (B_K + w), 1);
        asm volatile("fence.mbarrier_init.release.cluster;" ::: "memory");
        mbar_expect(bar + 8 * (B_K + w), 16384);
        tma3d(sb + SM_KV + w * 16384, &mp.k, 0, row, 0, bar + 8 * (B_K + w));
        TL(41);
        mbar_expect(bar + 8 * (B_WQ + w), 8192);
        tma2d(sb + SM_W + w * 8192, &mp.wq, 512 * g + 64 * w, 64 * c.rank, bar + 8 * (B_WQ + w));
        TL(42);
    }
    __syncwarp();
    asm volatile("ld.relaxed.gpu.global.u32 %0, [%1];" : "=r"(c.tag) : "l"(&g_epoch) : "memory");
    unsigned short x0raw = 0;
    if (isA && c.tid < 64) asm volatile("ld.global.nc.u16 %0, [%1];" : "=h"(x0raw) : "l"(xin + 64 * c.rank + pos2col(c.tid)) : "memory");
    if (c.lane < 6) {
        const int i = c.warp * 6 + c.lane;
        if (i < NBAR && !(isA && i < 16)) {
            mbar_init(bar + 8 * i, i >= B_LS ? 8 : 1);
            asm volatile("fence.mbarrier_init.release.cluster;" ::: "memory");
            if (i >= B_RSQ && i < B_LS) {
                const uint32_t bytes = (i == B_RSQ) ? 4160 : (i == B_RSQ + 1) ? 2112 : (i < B_RSO) ? 1024 : (i < B_RSX || i == B_RSO2) ? 2304 : (i == B_MX) ? 128 : 2048;
                mbar_expect(bar + 8 * i, bytes);
            }
        }
    } else if (c.lane == 7 && c.warp == 0) {
        sts32(sb + SM_ZERO, 0);
    } else if (c.lane == 6 && c.warp < 3) {
        const int idx = isA ? (c.warp == 0 ? 1 : c.warp + 2) : 5 + c.warp;
        asm volatile("prefetch.tensormap [%0];" ::"l"((u64)(&mp.k + idx)) : "memory");
    }
    TL(11);
    __syncthreads();
    TL(12);
    asm volatile("barrier.cluster.arrive.relaxed.aligned;" ::: "memory");
    asm volatile("barrier.cluster.wait.aligned;" ::: "memory");
    TL(23);

    if (isA) {
        uint32_t kf[4][8][4];
        float cs = 0.f;
        attn_layer<0>(c, mp, x0raw, kf, cs);
        attn_layer<1>(c, mp, x0raw, kf, cs);
        if (c.cid == 0 && c.tid < 64) {
            bf16* op = out + 64 * c.rank + pos2col(c.tid);
            asm volatile("" : "+l"(op));
            *op = __float2bfloat16(poll_sum<NF>(&g_fa[1][c.rank][0][c.tid], c.tag));
            if (c.rank == 0 && c.tid == 0)
                asm volatile("st.relaxed.gpu.global.u32 [%0], %1;" ::"l"(&g_epoch), "r"(c.tag + 1 + (c.tag == 0xffffffffu)) : "memory");
        }
        TL(24);
    } else {
        const int fc = c.cid - NA;
        uint32_t w13[4][4][4], w2[4][2][4];
        float cs = 0.f;
        if (c.tid == 0) {
            while (clock64() - t0 < F_DELAY) {}
            int it = 0;
            while ((unsigned)(ld_pkt(&g_go[fc * CL + c.rank][0]) >> 32) != c.tag && ++it < SPIN_LIMIT) {}
            const long long t1 = clock64();
            while (clock64() - t1 < F_LAG) {}
            mbar_expect(bar + 8 * B_W1, 32768);
            tma3d(sb + SM_W1, &mp.w1, 0, 64 * c.rank, 4 * fc, bar + 8 * B_W1);
            mbar_expect(bar + 8 * B_W3, 32768);
            tma3d(sb + SM_W3, &mp.w3, 0, 64 * c.rank, 4 * fc, bar + 8 * B_W3);
            mbar_expect(bar + 8 * B_W2, 32768);
            tma3d(sb + SM_W2, &mp.w2, 0, 256 * fc + 32 * c.rank, 0, bar + 8 * B_W2);
        }
        __syncwarp();
        ffn_layer<0>(c, w13, w2, cs);
        ffn_layer<1>(c, w13, w2, cs);
    }
}

__device__ float fb_x[2][D_], fb_q[4096], fb_o[4096], fb_h[FF_];
constexpr int FB_SPL = 32;
__device__ float fb_part[32][FB_SPL][DH_ + 2];

__device__ __forceinline__ void fb_ln(const float* x, float* xn, float* red) {
    const int t = threadIdx.x;
    float a = x[t], b = x[t + 256];
    float s = a + b;
    for (int o = 16; o; o >>= 1) s += __shfl_xor_sync(~0u, s, o);
    if ((t & 31) == 0) red[t >> 5] = s;
    __syncthreads();
    float m = 0.f; for (int i = 0; i < 8; i++) m += red[i];
    m *= (1.f / D_);
    __syncthreads();
    float v = (a - m) * (a - m) + (b - m) * (b - m);
    for (int o = 16; o; o >>= 1) v += __shfl_xor_sync(~0u, v, o);
    if ((t & 31) == 0) red[t >> 5] = v;
    __syncthreads();
    float var = 0.f; for (int i = 0; i < 8; i++) var += red[i];
    const float r = rsqrtf(var * (1.f / D_) + LN_EPS);
    xn[t] = (a - m) * r; xn[t + 256] = (b - m) * r;
    __syncthreads();
}
__global__ void fb_init(const bf16* x) { fb_x[0][threadIdx.x] = __bfloat162float(x[threadIdx.x]); }
__global__ void fb_qk(const bf16* wq) {
    __shared__ float xn[D_], red[8], part[8][32];
    fb_ln(fb_x[0], xn, red);
    const int col = blockIdx.x * 32 + (threadIdx.x & 31), kg = threadIdx.x >> 5;
    float s = 0.f;
    for (int k = kg * 64; k < kg * 64 + 64; k++) s += xn[k] * __bfloat162float(wq[(size_t)k * 4096 + col]);
    part[kg][threadIdx.x & 31] = s;
    __syncthreads();
    if (threadIdx.x < 32) { float v = 0.f; for (int i = 0; i < 8; i++) v += part[i][threadIdx.x]; fb_q[col] = v * QSCALE; }
}
__global__ void fb_attn(const bf16* kc, const bf16* vc) {
    __shared__ float p[4][128], acc[4][4][DH_];
    const int g = blockIdx.x, sp = blockIdx.y, t = threadIdx.x, lane = t & 31, w = t >> 5;
    const size_t row0 = (size_t)g * SK_ + (SK_ - WIN_) + sp * 128;
    float q[4][4];
#pragma unroll
    for (int h = 0; h < 4; h++)
#pragma unroll
        for (int j = 0; j < 4; j++) q[h][j] = fb_q[(4 * g + h) * DH_ + lane * 4 + j];
#pragma unroll 4
    for (int k = w * 16; k < w * 16 + 16; k++) {
        const uint2 kv = *(const uint2*)(kc + (row0 + k) * DH_ + lane * 4);
        const float k0 = __uint_as_float(kv.x << 16), k1 = __uint_as_float(kv.x & 0xffff0000u);
        const float k2 = __uint_as_float(kv.y << 16), k3 = __uint_as_float(kv.y & 0xffff0000u);
#pragma unroll
        for (int h = 0; h < 4; h++) {
            float s = q[h][0] * k0 + q[h][1] * k1 + q[h][2] * k2 + q[h][3] * k3;
            for (int o = 16; o; o >>= 1) s += __shfl_xor_sync(~0u, s, o);
            if (lane == 0) p[h][k] = s;
        }
    }
    __syncthreads();
    if (w < 4) {
        float v[4], m;
#pragma unroll
        for (int j = 0; j < 4; j++) v[j] = p[w][lane + 32 * j];
        m = fmaxf(fmaxf(v[0], v[1]), fmaxf(v[2], v[3]));
        for (int o = 16; o; o >>= 1) m = fmaxf(m, __shfl_xor_sync(~0u, m, o));
        float l = 0.f;
#pragma unroll
        for (int j = 0; j < 4; j++) { v[j] = exp2f(v[j] - m); p[w][lane + 32 * j] = v[j]; l += v[j]; }
        for (int o = 16; o; o >>= 1) l += __shfl_xor_sync(~0u, l, o);
        if (lane == 0) { fb_part[4 * g + w][sp][DH_] = m; fb_part[4 * g + w][sp][DH_ + 1] = l; }
    }
    __syncthreads();
    {
        const int d = (t & 63) * 2, kg = t >> 6;
        float o[4][2] = {};
#pragma unroll 4
        for (int k = kg * 32; k < kg * 32 + 32; k++) {
            const unsigned vv = *(const unsigned*)(vc + (row0 + k) * DH_ + d);
            const float v0 = __uint_as_float(vv << 16), v1 = __uint_as_float(vv & 0xffff0000u);
#pragma unroll
            for (int h = 0; h < 4; h++) { o[h][0] += p[h][k] * v0; o[h][1] += p[h][k] * v1; }
        }
#pragma unroll
        for (int h = 0; h < 4; h++) { acc[kg][h][d] = o[h][0]; acc[kg][h][d + 1] = o[h][1]; }
    }
    __syncthreads();
    for (int i = t; i < 4 * DH_; i += 256) {
        const int h = i >> 7, d = i & 127;
        fb_part[4 * g + h][sp][d] = (acc[0][h][d] + acc[1][h][d]) + (acc[2][h][d] + acc[3][h][d]);
    }
}
__global__ void fb_comb() {
    const int h = blockIdx.x, t = threadIdx.x;
    float M = fb_part[h][0][DH_];
    for (int s = 1; s < FB_SPL; s++) M = fmaxf(M, fb_part[h][s][DH_]);
    float num = 0.f, den = 0.f;
    for (int s = 0; s < FB_SPL; s++) { const float f = exp2f(fb_part[h][s][DH_] - M); num += f * fb_part[h][s][t]; den += f * fb_part[h][s][DH_ + 1]; }
    fb_o[h * DH_ + t] = num / den;
}
__global__ void fb_proj(const bf16* W, int K, int which, bf16* out) {
    __shared__ float part[64][17];
    const float* v = which == 0 ? fb_o : fb_h;
    const int cl = threadIdx.x & 15, col = blockIdx.x * 16 + cl, kg = threadIdx.x >> 4;
    float s = 0.f;
#pragma unroll 4
    for (int k = kg; k < K; k += 64) s += v[k] * __bfloat162float(W[(size_t)k * D_ + col]);
    part[kg][cl] = s;
    __syncthreads();
    if (threadIdx.x < 16) {
        float y = fb_x[which][col];
        for (int i = 0; i < 64; i++) y += part[i][threadIdx.x];
        const bf16 yb = __float2bfloat16(y);
        fb_x[which ^ 1][col] = __bfloat162float(yb);
        if (out) out[col] = yb;
    }
}
__global__ void fb_ffn1(const bf16* w1, const bf16* w3) {
    __shared__ float xn[D_], red[8], pg[8][32], pu[8][32];
    fb_ln(fb_x[1], xn, red);
    const int col = blockIdx.x * 32 + (threadIdx.x & 31), kg = threadIdx.x >> 5;
    float a = 0.f, b = 0.f;
    for (int k = kg * 64; k < kg * 64 + 64; k++) {
        a += xn[k] * __bfloat162float(w1[(size_t)k * FF_ + col]);
        b += xn[k] * __bfloat162float(w3[(size_t)k * FF_ + col]);
    }
    pg[kg][threadIdx.x & 31] = a; pu[kg][threadIdx.x & 31] = b;
    __syncthreads();
    if (threadIdx.x < 32) {
        float gt = 0.f, up = 0.f;
        for (int i = 0; i < 8; i++) { gt += pg[i][threadIdx.x]; up += pu[i][threadIdx.x]; }
        fb_h[col] = gt / (1.f + __expf(-gt)) * up;
    }
}

typedef CUresult (*EncodeFn)(CUtensorMap*, CUtensorMapDataType, cuuint32_t, void*, const cuuint64_t*, const cuuint64_t*,
                             const cuuint32_t*, const cuuint32_t*, CUtensorMapInterleave, CUtensorMapSwizzle,
                             CUtensorMapL2promotion, CUtensorMapFloatOOBfill);

bool make_map(EncodeFn enc, CUtensorMap* m, const void* p, int rank, const cuuint64_t* dims, const cuuint64_t* strides,
              const cuuint32_t* box) {
    const cuuint32_t es[4] = {1, 1, 1, 1};
    return enc(m, CU_TENSOR_MAP_DATA_TYPE_BFLOAT16, rank, const_cast<void*>(p), dims, strides, box, es,
               CU_TENSOR_MAP_INTERLEAVE_NONE, CU_TENSOR_MAP_SWIZZLE_128B, CU_TENSOR_MAP_L2_PROMOTION_L2_256B,
               CU_TENSOR_MAP_FLOAT_OOB_FILL_NONE) == CUDA_SUCCESS;
}

}

extern "C" void kernel_launch(void* const* d_in, const int* in_sizes, int n_in, void* d_out, int out_size) {
    const bf16* x = (const bf16*)d_in[0];
    const bf16* kc = (const bf16*)d_in[1];
    const bf16* vc = (const bf16*)d_in[2];
    const bf16* wq = (const bf16*)d_in[3];
    const bf16* wo = (const bf16*)d_in[4];
    const bf16* w1 = (const bf16*)d_in[6];
    const bf16* w3 = (const bf16*)d_in[7];
    const bf16* w2 = (const bf16*)d_in[8];
    bf16* out = (bf16*)d_out;
    cudaStream_t st = cudaStreamPerThread;

    cudaLaunchConfig_t cfg = {};
    cfg.gridDim = dim3((NA + NF) * CL); cfg.blockDim = dim3(NT); cfg.dynamicSmemBytes = SM_TOTAL; cfg.stream = st;
    cudaLaunchAttribute at[1];
    at[0].id = cudaLaunchAttributeClusterDimension;
    at[0].val.clusterDim.x = CL; at[0].val.clusterDim.y = 1; at[0].val.clusterDim.z = 1;
    cfg.attrs = at; cfg.numAttrs = 1;

    static int mode = -1;
    static EncodeFn enc = nullptr;
    if (mode < 0) {
        mode = 0;
        void* fn = nullptr;
        cudaDriverEntryPointQueryResult qr;
        int ncl = 0;
        if (cudaFuncSetAttribute(fused_kernel, cudaFuncAttributeMaxDynamicSharedMemorySize, SM_TOTAL) == cudaSuccess &&
            cudaOccupancyMaxActiveClusters(&ncl, fused_kernel, &cfg) == cudaSuccess && ncl >= NA + NF &&
            cudaGetDriverEntryPoint("cuTensorMapEncodeTiled", &fn, cudaEnableDefault, &qr) == cudaSuccess && fn) {
            enc = (EncodeFn)fn;
            mode = 1;
        }
        (void)cudaGetLastError();
    }
    bool ok = mode == 1;
    Maps mp;
    if (ok) {
        const cuuint32_t bkv[3] = {64, 64, 2}, bwq[2] = {64, 64}, bwq8[3] = {64, 64, 8}, bwo[4] = {64, 16, 4, 8};
        const cuuint32_t bw1[3] = {64, 64, 4}, bw2[3] = {64, 32, 8};
        const cuuint64_t dkv[3] = {64, (cuuint64_t)HKV_ * SK_, 2}, skv[2] = {256, 128};
        const cuuint64_t dwq[2] = {4096, 512}, swq[1] = {8192};
        const cuuint64_t dwq8[3] = {64, 512, 64}, swq8[2] = {8192, 128};
        const cuuint64_t dwo[4] = {64, 128, 32, 8}, swo[3] = {1024, 131072, 128};
        const cuuint64_t dw1[3] = {64, 512, FF_ / 64}, sw1[2] = {FF_ * 2, 128};
        const cuuint64_t dw2[3] = {64, FF_, 8}, sw2[2] = {1024, 128};
        ok = make_map(enc, &mp.k, kc, 3, dkv, skv, bkv) && make_map(enc, &mp.v, vc, 3, dkv, skv, bkv) &&
             make_map(enc, &mp.wq, wq, 2, dwq, swq, bwq) && make_map(enc, &mp.wq8, wq, 3, dwq8, swq8, bwq8) &&
             make_map(enc, &mp.wo, wo, 4, dwo, swo, bwo) &&
             make_map(enc, &mp.w1, w1, 3, dw1, sw1, bw1) && make_map(enc, &mp.w3, w3, 3, dw1, sw1, bw1) &&
             make_map(enc, &mp.w2, w2, 3, dw2, sw2, bw2);
    }
    if (ok) {
        cudaLaunchKernelEx(&cfg, fused_kernel, (const char*)kc, x, out, mp);
        return;
    }
    fb_init<<<1, D_, 0, st>>>(x);
    for (int l = 0; l < 2; l++) {
        fb_qk<<<128, 256, 0, st>>>(wq);
        fb_attn<<<dim3(8, FB_SPL), 256, 0, st>>>(kc, vc);
        fb_comb<<<32, 128, 0, st>>>();
        fb_proj<<<32, 1024, 0, st>>>(wo, 4096, 0, nullptr);
        fb_ffn1<<<56, 256, 0, st>>>(w1, w3);
        fb_proj<<<32, 1024, 0, st>>>(w2, FF_, 1, l == 1 ? out : nullptr);
    }
}
```
